```python
import torch

def _softmax(x, axis=-1):
    return torch.softmax(x, dim=axis)
def _gelu(x):
    return torch.nn.functional.gelu(x, approximate="tanh")
def _silu(x):
    return torch.nn.functional.silu(x)
def _sigmoid(x):
    return torch.sigmoid(x)
def _layernorm(x, axis=-1, eps=1e-5):
    m = x.mean(dim=axis, keepdim=True)
    v = x.var(dim=axis, keepdim=True, unbiased=False)
    return (x - m) / torch.sqrt(v + eps)
def _scatter_add(tgt, idx, src, axis=0):
    return tgt.clone().index_add_(axis, idx, src)
def _segment_sum(src, seg, n):
    out = torch.zeros((n,) + src.shape[1:], dtype=src.dtype)
    return out.index_add_(0, seg, src)
def _pad(x, pw):
    flat = tuple(v for pair in reversed(pw) for v in pair)
    return torch.nn.functional.pad(x, flat)

kernel_name = 'recurrent_scan__grouped_kv_mqa__dense_activation_squared_relu__prompt'

def setup_inputs():

    _w = (lambda a: (lambda t: t.to(torch.bfloat16) if t.is_floating_point() else t)(torch.as_tensor(a)))
    def _A_setup():
        B, S, D, H = 1, 2048, 512, 32
        Dh = D // H
        return {
            "x": _w((lambda *s: torch.randn(*s, dtype=torch.bfloat16) * 0.05)(B, S, D)),
            "wq": _w((lambda *s: torch.randn(*s, dtype=torch.bfloat16) * 0.05)(D, H * Dh)),
            "wk": _w((lambda *s: torch.randn(*s, dtype=torch.bfloat16) * 0.05)(D, Dh)),
            "wv": _w((lambda *s: torch.randn(*s, dtype=torch.bfloat16) * 0.05)(D, Dh)),
            "wo": _w((lambda *s: torch.randn(*s, dtype=torch.bfloat16) * 0.05)(H * Dh, D)),
        }
    _A_in = _A_setup()

    def _B_setup():
        B, S, D, F = 1, 2048, 512, 1792
        return {
            "x": _w((lambda *s: torch.randn(*s, dtype=torch.bfloat16) * 0.05)(B, S, D)),
            "w1": _w((lambda *s: torch.randn(*s, dtype=torch.bfloat16) * 0.05)(D, F)),
            "b1": _w((lambda *s: torch.randn(*s, dtype=torch.bfloat16) * 0.4)(F)),
            "w2": _w((lambda *s: torch.randn(*s, dtype=torch.bfloat16) * 0.05)(F, D)),
            "b2": _w((lambda *s: torch.randn(*s, dtype=torch.bfloat16) * 1.6)(D)),
        }
    _B_in = _B_setup()

    return {
        "A_x": _A_in["x"],
        "A_wq": _A_in["wq"],
        "A_wk": _A_in["wk"],
        "A_wv": _A_in["wv"],
        "A_wo": _A_in["wo"],
        "B_x": _B_in["x"],
        "B_w1": _B_in["w1"],
        "B_b1": _B_in["b1"],
        "B_w2": _B_in["w2"],
        "B_b2": _B_in["b2"],
    }

def reference(A_x, A_wq, A_wk, A_wv, A_wo, B_x, B_w1, B_b1, B_w2, B_b2):
    def _A_ref(x, wq, wk, wv, wo):
        B, S, D = x.shape
        H = 32
        Dh = D // H
        q = (lambda x, *d: x.permute(*d))((x @ wq).reshape(B, S, H, Dh), 0, 2, 1, 3)
        k = x @ wk
        v = x @ wv
        scores = torch.einsum("bhqd,bkd->bhqk", q, k) * (Dh ** -0.5)
        p = _softmax(scores, axis=-1)
        o = torch.einsum("bhqk,bkd->bhqd", p, v)
        return (lambda x, *d: x.permute(*d))(o, 0, 2, 1, 3).reshape(B, S, H * Dh) @ wo

    def _B_ref(x, w1, b1, w2, b2):
        h = torch.einsum("bsd,df->bsf", x, w1) + b1
        zero = torch.zeros_like(h)
        r = torch.where(h > zero, h, zero)
        h = r * r
        out = torch.einsum("bsf,fd->bsd", h, w2) + b2
        return out

    x = A_x
    xn = _layernorm(x, axis=-1)
    s = _A_ref(xn, A_wq, A_wk, A_wv, A_wo)
    g = _silu(_B_ref(xn, B_w1, B_b1, B_w2, B_b2))
    return x + s * g
```

```cpp
#include <cuda_runtime.h>
#include <cuda_bf16.h>
#include <cuda_fp16.h>
#include <cuda.h>
#include <stdint.h>

namespace {

constexpr int SEQ = 2048, DM = 512, FF = 1792;
constexpr int NCTA = 128;
constexpr int NTHREADS = 640;

constexpr int SM_XN   = 0;
constexpr int NGS     = 4;
constexpr int GSTAGE  = 24576;
constexpr int SM_RING = 65536;
constexpr int NKS     = 4;
constexpr int KSTAGE  = 10240;
constexpr int SM_KVR  = SM_RING + NGS * GSTAGE;
constexpr int SM_STG  = SM_KVR + NKS * KSTAGE;
constexpr int SM_BIAS = SM_STG + 16384;
constexpr int SM_BAR  = SM_BIAS + 1152;
constexpr int SM_END  = SM_BAR + 256;
constexpr int SMEM_BYTES = SM_END + 1024;
constexpr int SM_XT   = SM_XN;
constexpr int SM_G    = SM_XN + 16384;

constexpr int B_GFULL = 0, B_GEMPTY = 4, B_KFULL = 8, B_KEMPTY = 12, B_XT = 16;

constexpr int NKBLK = 76;

__device__ __align__(1024) unsigned char g_kv[16 * 8192];
__device__ __align__(16) __nv_bfloat16 g_kb[SEQ * 16];
__device__ __align__(16) float g_kmax[NCTA];
__device__ __align__(16) float g_vmax[NCTA];
__device__ __align__(1024) __nv_bfloat16 g_h[SEQ * FF];
__device__ __align__(1024) __nv_bfloat16 g_o[SEQ * DM];
__device__ unsigned g_cnt_kv;
__device__ unsigned g_cnt_end;
__device__ unsigned g_cnt_h[NCTA];
__device__ unsigned g_cnt_o[NCTA * 2];

struct Params {
  CUtensorMap wq, w1, w2, wo, h, o, x, out;
};

template<int N> __device__ __forceinline__ void qk32(float* d, const uint32_t* a, uint64_t db);
template<int N> __device__ __forceinline__ void qk16(uint32_t* d, const uint32_t* a, uint64_t db);
template<int N> __device__ __forceinline__ void gemm_ss(float* d, uint64_t da, uint64_t db, int sc);
template<> __device__ __forceinline__ void qk32<16>(float* d, const uint32_t* a, uint64_t db) {
  asm volatile("{ .reg .pred p; setp.ne.b32 p, 0, 0;\n wgmma.mma_async.sync.aligned.m64n16k16.f32.f16.f16 {%0,%1,%2,%3,%4,%5,%6,%7}, {%8,%9,%10,%11}, %12, p, 1, 1, 0; }\n"
   : "=f"(d[0]),"=f"(d[1]),"=f"(d[2]),"=f"(d[3]),"=f"(d[4]),"=f"(d[5]),"=f"(d[6]),"=f"(d[7]) : "r"(a[0]),"r"(a[1]),"r"(a[2]),"r"(a[3]),"l"(db));
}
template<> __device__ __forceinline__ void qk16<16>(uint32_t* d, const uint32_t* a, uint64_t db) {
  asm volatile("{ .reg .pred p; setp.ne.b32 p, 0, 0;\n wgmma.mma_async.sync.aligned.m64n16k16.f16.f16.f16 {%0,%1,%2,%3}, {%4,%5,%6,%7}, %8, p, 1, 1, 0; }\n"
   : "=r"(d[0]),"=r"(d[1]),"=r"(d[2]),"=r"(d[3]) : "r"(a[0]),"r"(a[1]),"r"(a[2]),"r"(a[3]),"l"(db));
}
template<> __device__ __forceinline__ void qk32<32>(float* d, const uint32_t* a, uint64_t db) {
  asm volatile("{ .reg .pred p; setp.ne.b32 p, 0, 0;\n wgmma.mma_async.sync.aligned.m64n32k16.f32.f16.f16 {%0,%1,%2,%3,%4,%5,%6,%7,%8,%9,%10,%11,%12,%13,%14,%15}, {%16,%17,%18,%19}, %20, p, 1, 1, 0; }\n"
   : "=f"(d[0]),"=f"(d[1]),"=f"(d[2]),"=f"(d[3]),"=f"(d[4]),"=f"(d[5]),"=f"(d[6]),"=f"(d[7]),"=f"(d[8]),"=f"(d[9]),"=f"(d[10]),"=f"(d[11]),"=f"(d[12]),"=f"(d[13]),"=f"(d[14]),"=f"(d[15]) : "r"(a[0]),"r"(a[1]),"r"(a[2]),"r"(a[3]),"l"(db));
}
template<> __device__ __forceinline__ void qk16<32>(uint32_t* d, const uint32_t* a, uint64_t db) {
  asm volatile("{ .reg .pred p; setp.ne.b32 p, 0, 0;\n wgmma.mma_async.sync.aligned.m64n32k16.f16.f16.f16 {%0,%1,%2,%3,%4,%5,%6,%7}, {%8,%9,%10,%11}, %12, p, 1, 1, 0; }\n"
   : "=r"(d[0]),"=r"(d[1]),"=r"(d[2]),"=r"(d[3]),"=r"(d[4]),"=r"(d[5]),"=r"(d[6]),"=r"(d[7]) : "r"(a[0]),"r"(a[1]),"r"(a[2]),"r"(a[3]),"l"(db));
}
template<> __device__ __forceinline__ void qk32<48>(float* d, const uint32_t* a, uint64_t db) {
  asm volatile("{ .reg .pred p; setp.ne.b32 p, 0, 0;\n wgmma.mma_async.sync.aligned.m64n48k16.f32.f16.f16 {%0,%1,%2,%3,%4,%5,%6,%7,%8,%9,%10,%11,%12,%13,%14,%15,%16,%17,%18,%19,%20,%21,%22,%23}, {%24,%25,%26,%27}, %28, p, 1, 1, 0; }\n"
   : "=f"(d[0]),"=f"(d[1]),"=f"(d[2]),"=f"(d[3]),"=f"(d[4]),"=f"(d[5]),"=f"(d[6]),"=f"(d[7]),"=f"(d[8]),"=f"(d[9]),"=f"(d[10]),"=f"(d[11]),"=f"(d[12]),"=f"(d[13]),"=f"(d[14]),"=f"(d[15]),"=f"(d[16]),"=f"(d[17]),"=f"(d[18]),"=f"(d[19]),"=f"(d[20]),"=f"(d[21]),"=f"(d[22]),"=f"(d[23]) : "r"(a[0]),"r"(a[1]),"r"(a[2]),"r"(a[3]),"l"(db));
}
template<> __device__ __forceinline__ void qk16<48>(uint32_t* d, const uint32_t* a, uint64_t db) {
  asm volatile("{ .reg .pred p; setp.ne.b32 p, 0, 0;\n wgmma.mma_async.sync.aligned.m64n48k16.f16.f16.f16 {%0,%1,%2,%3,%4,%5,%6,%7,%8,%9,%10,%11}, {%12,%13,%14,%15}, %16, p, 1, 1, 0; }\n"
   : "=r"(d[0]),"=r"(d[1]),"=r"(d[2]),"=r"(d[3]),"=r"(d[4]),"=r"(d[5]),"=r"(d[6]),"=r"(d[7]),"=r"(d[8]),"=r"(d[9]),"=r"(d[10]),"=r"(d[11]) : "r"(a[0]),"r"(a[1]),"r"(a[2]),"r"(a[3]),"l"(db));
}
template<> __device__ __forceinline__ void qk32<64>(float* d, const uint32_t* a, uint64_t db) {
  asm volatile("{ .reg .pred p; setp.ne.b32 p, 0, 0;\n wgmma.mma_async.sync.aligned.m64n64k16.f32.f16.f16 {%0,%1,%2,%3,%4,%5,%6,%7,%8,%9,%10,%11,%12,%13,%14,%15,%16,%17,%18,%19,%20,%21,%22,%23,%24,%25,%26,%27,%28,%29,%30,%31}, {%32,%33,%34,%35}, %36, p, 1, 1, 0; }\n"
   : "=f"(d[0]),"=f"(d[1]),"=f"(d[2]),"=f"(d[3]),"=f"(d[4]),"=f"(d[5]),"=f"(d[6]),"=f"(d[7]),"=f"(d[8]),"=f"(d[9]),"=f"(d[10]),"=f"(d[11]),"=f"(d[12]),"=f"(d[13]),"=f"(d[14]),"=f"(d[15]),"=f"(d[16]),"=f"(d[17]),"=f"(d[18]),"=f"(d[19]),"=f"(d[20]),"=f"(d[21]),"=f"(d[22]),"=f"(d[23]),"=f"(d[24]),"=f"(d[25]),"=f"(d[26]),"=f"(d[27]),"=f"(d[28]),"=f"(d[29]),"=f"(d[30]),"=f"(d[31]) : "r"(a[0]),"r"(a[1]),"r"(a[2]),"r"(a[3]),"l"(db));
}
template<> __device__ __forceinline__ void qk16<64>(uint32_t* d, const uint32_t* a, uint64_t db) {
  asm volatile("{ .reg .pred p; setp.ne.b32 p, 0, 0;\n wgmma.mma_async.sync.aligned.m64n64k16.f16.f16.f16 {%0,%1,%2,%3,%4,%5,%6,%7,%8,%9,%10,%11,%12,%13,%14,%15}, {%16,%17,%18,%19}, %20, p, 1, 1, 0; }\n"
   : "=r"(d[0]),"=r"(d[1]),"=r"(d[2]),"=r"(d[3]),"=r"(d[4]),"=r"(d[5]),"=r"(d[6]),"=r"(d[7]),"=r"(d[8]),"=r"(d[9]),"=r"(d[10]),"=r"(d[11]),"=r"(d[12]),"=r"(d[13]),"=r"(d[14]),"=r"(d[15]) : "r"(a[0]),"r"(a[1]),"r"(a[2]),"r"(a[3]),"l"(db));
}
__device__ __forceinline__ void pv24(float* d, const uint32_t* a, uint64_t db) {
  asm volatile("{ .reg .pred p; setp.eq.b32 p, 0, 0;\n wgmma.mma_async.sync.aligned.m64n24k16.f32.bf16.bf16 {%0,%1,%2,%3,%4,%5,%6,%7,%8,%9,%10,%11}, {%12,%13,%14,%15}, %16, p, 1, 1, 1; }\n"
   : "+f"(d[0]),"+f"(d[1]),"+f"(d[2]),"+f"(d[3]),"+f"(d[4]),"+f"(d[5]),"+f"(d[6]),"+f"(d[7]),"+f"(d[8]),"+f"(d[9]),"+f"(d[10]),"+f"(d[11]) : "r"(a[0]),"r"(a[1]),"r"(a[2]),"r"(a[3]),"l"(db));
}
template<> __device__ __forceinline__ void gemm_ss<32>(float* d, uint64_t da, uint64_t db, int sc) {
  asm volatile("{ .reg .pred p; setp.ne.b32 p, %18, 0;\n wgmma.mma_async.sync.aligned.m64n32k16.f32.bf16.bf16 {%0,%1,%2,%3,%4,%5,%6,%7,%8,%9,%10,%11,%12,%13,%14,%15}, %16, %17, p, 1, 1, 0, 1; }\n"
   : "+f"(d[0]),"+f"(d[1]),"+f"(d[2]),"+f"(d[3]),"+f"(d[4]),"+f"(d[5]),"+f"(d[6]),"+f"(d[7]),"+f"(d[8]),"+f"(d[9]),"+f"(d[10]),"+f"(d[11]),"+f"(d[12]),"+f"(d[13]),"+f"(d[14]),"+f"(d[15]) : "l"(da),"l"(db),"r"(sc));
}
template<> __device__ __forceinline__ void gemm_ss<64>(float* d, uint64_t da, uint64_t db, int sc) {
  asm volatile("{ .reg .pred p; setp.ne.b32 p, %34, 0;\n wgmma.mma_async.sync.aligned.m64n64k16.f32.bf16.bf16 {%0,%1,%2,%3,%4,%5,%6,%7,%8,%9,%10,%11,%12,%13,%14,%15,%16,%17,%18,%19,%20,%21,%22,%23,%24,%25,%26,%27,%28,%29,%30,%31}, %32, %33, p, 1, 1, 0, 1; }\n"
   : "+f"(d[0]),"+f"(d[1]),"+f"(d[2]),"+f"(d[3]),"+f"(d[4]),"+f"(d[5]),"+f"(d[6]),"+f"(d[7]),"+f"(d[8]),"+f"(d[9]),"+f"(d[10]),"+f"(d[11]),"+f"(d[12]),"+f"(d[13]),"+f"(d[14]),"+f"(d[15]),"+f"(d[16]),"+f"(d[17]),"+f"(d[18]),"+f"(d[19]),"+f"(d[20]),"+f"(d[21]),"+f"(d[22]),"+f"(d[23]),"+f"(d[24]),"+f"(d[25]),"+f"(d[26]),"+f"(d[27]),"+f"(d[28]),"+f"(d[29]),"+f"(d[30]),"+f"(d[31]) : "l"(da),"l"(db),"r"(sc));
}
template<> __device__ __forceinline__ void gemm_ss<128>(float* d, uint64_t da, uint64_t db, int sc) {
  asm volatile("{ .reg .pred p; setp.ne.b32 p, %66, 0;\n wgmma.mma_async.sync.aligned.m64n128k16.f32.bf16.bf16 {%0,%1,%2,%3,%4,%5,%6,%7,%8,%9,%10,%11,%12,%13,%14,%15,%16,%17,%18,%19,%20,%21,%22,%23,%24,%25,%26,%27,%28,%29,%30,%31,%32,%33,%34,%35,%36,%37,%38,%39,%40,%41,%42,%43,%44,%45,%46,%47,%48,%49,%50,%51,%52,%53,%54,%55,%56,%57,%58,%59,%60,%61,%62,%63}, %64, %65, p, 1, 1, 0, 1; }\n"
   : "+f"(d[0]),"+f"(d[1]),"+f"(d[2]),"+f"(d[3]),"+f"(d[4]),"+f"(d[5]),"+f"(d[6]),"+f"(d[7]),"+f"(d[8]),"+f"(d[9]),"+f"(d[10]),"+f"(d[11]),"+f"(d[12]),"+f"(d[13]),"+f"(d[14]),"+f"(d[15]),"+f"(d[16]),"+f"(d[17]),"+f"(d[18]),"+f"(d[19]),"+f"(d[20]),"+f"(d[21]),"+f"(d[22]),"+f"(d[23]),"+f"(d[24]),"+f"(d[25]),"+f"(d[26]),"+f"(d[27]),"+f"(d[28]),"+f"(d[29]),"+f"(d[30]),"+f"(d[31]),"+f"(d[32]),"+f"(d[33]),"+f"(d[34]),"+f"(d[35]),"+f"(d[36]),"+f"(d[37]),"+f"(d[38]),"+f"(d[39]),"+f"(d[40]),"+f"(d[41]),"+f"(d[42]),"+f"(d[43]),"+f"(d[44]),"+f"(d[45]),"+f"(d[46]),"+f"(d[47]),"+f"(d[48]),"+f"(d[49]),"+f"(d[50]),"+f"(d[51]),"+f"(d[52]),"+f"(d[53]),"+f"(d[54]),"+f"(d[55]),"+f"(d[56]),"+f"(d[57]),"+f"(d[58]),"+f"(d[59]),"+f"(d[60]),"+f"(d[61]),"+f"(d[62]),"+f"(d[63]) : "l"(da),"l"(db),"r"(sc));
}


#define WG_FENCE()  asm volatile("wgmma.fence.sync.aligned;" ::: "memory")
#define WG_COMMIT() asm volatile("wgmma.commit_group.sync.aligned;" ::: "memory")
#define WG_WAIT(n)  asm volatile("wgmma.wait_group.sync.aligned " #n ";" ::: "memory")

template<int N> __device__ __forceinline__ void fence_regs(float* r) {
#pragma unroll
  for (int i = 0; i < N; i++) asm volatile("" : "+f"(r[i]) :: "memory");
}
template<int N> __device__ __forceinline__ void fence_regs(uint32_t* r) {
#pragma unroll
  for (int i = 0; i < N; i++) asm volatile("" : "+r"(r[i]) :: "memory");
}
__device__ __forceinline__ uint64_t mkdesc(uint32_t lo, uint32_t hi) {
  uint64_t d; asm("mov.b64 %0, {%1,%2};" : "=l"(d) : "r"(lo), "r"(hi)); return d;
}
__device__ __forceinline__ float ex2f(float x) { float y; asm("ex2.approx.ftz.f32 %0, %1;" : "=f"(y) : "f"(x)); return y; }
__device__ __forceinline__ uint32_t packbf(float lo, float hi) {
  uint32_t y; asm("cvt.rn.bf16x2.f32 %0, %1, %2;" : "=r"(y) : "f"(hi), "f"(lo)); return y;
}
__device__ __forceinline__ uint32_t packh(float lo, float hi) {
  uint32_t y; asm("cvt.rn.f16x2.f32 %0, %1, %2;" : "=r"(y) : "f"(hi), "f"(lo)); return y;
}
__device__ __forceinline__ float bflo(uint32_t v) { return __uint_as_float(v << 16); }
__device__ __forceinline__ float bfhi(uint32_t v) { return __uint_as_float(v & 0xffff0000u); }
__device__ __forceinline__ float bfr(float x) { return __bfloat162float(__float2bfloat16_rn(x)); }
__device__ __forceinline__ uint32_t hfma2(uint32_t a, uint32_t b, uint32_t c) {
  uint32_t y; asm("fma.rn.f16x2 %0, %1, %2, %3;" : "=r"(y) : "r"(a), "r"(b), "r"(c)); return y;
}
__device__ __forceinline__ uint32_t hadd2(uint32_t a, uint32_t b) {
  uint32_t y; asm("add.rn.f16x2 %0, %1, %2;" : "=r"(y) : "r"(a), "r"(b)); return y;
}
__device__ __forceinline__ uint32_t hsub2(uint32_t a, uint32_t b) {
  uint32_t y; asm("sub.rn.f16x2 %0, %1, %2;" : "=r"(y) : "r"(a), "r"(b)); return y;
}
__device__ __forceinline__ uint32_t badd2(uint32_t a, uint32_t b) {
  uint32_t y; asm("add.rn.bf16x2 %0, %1, %2;" : "=r"(y) : "r"(a), "r"(b)); return y;
}
__device__ __forceinline__ uint32_t bmul2(uint32_t a, uint32_t b) {
  uint32_t y; asm("mul.rn.bf16x2 %0, %1, %2;" : "=r"(y) : "r"(a), "r"(b)); return y;
}
__device__ __forceinline__ uint32_t badd2_relu(uint32_t a, uint32_t b) {
  uint32_t y; asm("fma.rn.relu.bf16x2 %0, %1, %2, %3;" : "=r"(y) : "r"(a), "r"(0x3f803f80u), "r"(b)); return y;
}

__device__ __forceinline__ uint32_t exp2_poly(uint32_t x) {
  uint32_t t  = hadd2(x, 0x66006600u);
  uint32_t nf = hsub2(t, 0x66006600u);
  uint32_t f  = hsub2(x, nf);
  uint32_t r  = hfma2(f, 0x20f920f9u, 0x297b297bu);
  r = hfma2(r, f, 0x2fd82fd8u);
  r = hfma2(r, f, 0x3f823fb5u);
  return (t << 7) + r;
}
constexpr float POLY_INV = 1.0f / 1.4140625f;

__device__ __forceinline__ void mbar_init(uint32_t a, int c) { asm volatile("mbarrier.init.shared.b64 [%0], %1;" :: "r"(a), "r"(c) : "memory"); }
__device__ __forceinline__ void mbar_expect(uint32_t a, uint32_t bytes) {
  asm volatile("mbarrier.arrive.expect_tx.shared.b64 _, [%0], %1;" :: "r"(a), "r"(bytes) : "memory");
}
__device__ __forceinline__ void mbar_arrive(uint32_t a) { asm volatile("mbarrier.arrive.shared.b64 _, [%0];" :: "r"(a) : "memory"); }
__device__ __forceinline__ bool mbar_test(uint32_t a, uint32_t ph) {
  uint32_t ok;
  asm volatile("{ .reg .pred p; mbarrier.test_wait.parity.shared.b64 p, [%1], %2; selp.u32 %0, 1, 0, p; }" : "=r"(ok) : "r"(a), "r"(ph) : "memory");
  return ok != 0;
}
__device__ __forceinline__ bool mbar_try(uint32_t a, uint32_t ph) {
  uint32_t ok;
  asm volatile("{ .reg .pred p; mbarrier.try_wait.parity.shared.b64 p, [%1], %2; selp.u32 %0, 1, 0, p; }" : "=r"(ok) : "r"(a), "r"(ph) : "memory");
  return ok != 0;
}
__device__ __forceinline__ void mbar_wait(uint32_t a, uint32_t ph) {
  if (mbar_try(a, ph)) return;
  int n = 0;
  while (!mbar_try(a, ph)) { if (++n > (1 << 22)) __trap(); }
}
__device__ __forceinline__ void bar_sync(int id, int n) { asm volatile("bar.sync %0, %1;" :: "r"(id), "r"(n) : "memory"); }
__device__ __forceinline__ void bar_arrive(int id, int n) { asm volatile("bar.arrive %0, %1;" :: "r"(id), "r"(n) : "memory"); }
__device__ __forceinline__ void fence_async() { asm volatile("fence.proxy.async;" ::: "memory"); }
__device__ __forceinline__ void fence_async_smem() { asm volatile("fence.proxy.async.shared::cta;" ::: "memory"); }
__device__ __forceinline__ unsigned ld_acquire(const unsigned* p) {
  unsigned v; asm volatile("ld.acquire.gpu.global.u32 %0, [%1];" : "=r"(v) : "l"(p) : "memory"); return v;
}
__device__ __forceinline__ void red_release(unsigned* p, unsigned v) {
  asm volatile("red.release.gpu.global.add.u32 [%0], %1;" :: "l"(p), "r"(v) : "memory");
}
__device__ __forceinline__ void tma_load(uint32_t dst, const CUtensorMap* m, int c0, int c1, uint32_t bar) {
  asm volatile("cp.async.bulk.tensor.2d.shared::cluster.global.mbarrier::complete_tx::bytes [%0], [%1, {%3, %4}], [%2];"
               :: "r"(dst), "l"(m), "r"(bar), "r"(c0), "r"(c1) : "memory");
}
__device__ __forceinline__ void tma_store(const CUtensorMap* m, int c0, int c1, uint32_t src) {
  asm volatile("cp.async.bulk.tensor.2d.global.shared::cta.bulk_group [%0, {%2, %3}], [%1];"
               :: "l"(m), "r"(src), "r"(c0), "r"(c1) : "memory");
}
__device__ __forceinline__ void tma_prefetch(const CUtensorMap* m, int c0, int c1) {
  asm volatile("cp.async.bulk.prefetch.tensor.2d.L2.global [%0, {%1, %2}];" :: "l"(m), "r"(c0), "r"(c1) : "memory");
}
__device__ __forceinline__ void bulk_load(uint32_t dst, const void* src, uint32_t bytes, uint32_t bar) {
  asm volatile("cp.async.bulk.shared::cluster.global.mbarrier::complete_tx::bytes [%0], [%1], %2, [%3];"
               :: "r"(dst), "l"(src), "r"(bytes), "r"(bar) : "memory");
}
__device__ __forceinline__ void stsm4(uint32_t addr, uint32_t a, uint32_t b, uint32_t c, uint32_t d) {
  asm volatile("stmatrix.sync.aligned.m8n8.x4.shared.b16 [%0], {%1,%2,%3,%4};" :: "r"(addr), "r"(a), "r"(b), "r"(c), "r"(d) : "memory");
}
__device__ __forceinline__ void sts32(uint32_t addr, uint32_t v) { asm volatile("st.shared.u32 [%0], %1;" :: "r"(addr), "r"(v) : "memory"); }
__device__ __forceinline__ uint32_t lds32(uint32_t addr) { uint32_t v; asm volatile("ld.shared.u32 %0, [%1];" : "=r"(v) : "r"(addr) : "memory"); return v; }
__device__ __forceinline__ void sts128(uint32_t addr, uint4 v) {
  asm volatile("st.shared.v4.u32 [%0], {%1,%2,%3,%4};" :: "r"(addr), "r"(v.x), "r"(v.y), "r"(v.z), "r"(v.w) : "memory");
}
__device__ __forceinline__ void mma16816(float* d, const uint32_t* a, uint32_t b0, uint32_t b1) {
  asm volatile("mma.sync.aligned.m16n8k16.row.col.f32.bf16.bf16.f32 {%0,%1,%2,%3}, {%4,%5,%6,%7}, {%8,%9}, {%0,%1,%2,%3};"
               : "+f"(d[0]), "+f"(d[1]), "+f"(d[2]), "+f"(d[3]) : "r"(a[0]), "r"(a[1]), "r"(a[2]), "r"(a[3]), "r"(b0), "r"(b1));
}

__device__ __forceinline__ uint32_t desc_lo(uint32_t addr, uint32_t lbo) { return ((addr & 0x3FFFF) >> 4) | ((lbo >> 4) << 16); }
constexpr uint32_t DHI_SW128 = (1024 >> 4) | (1u << 30);

__device__ __noinline__ void attn_slow(uint32_t q0, uint32_t q1, uint32_t q2, uint32_t q3, __nv_bfloat16* orow) {
  const int lane = threadIdx.x & 31, g = lane >> 2, t = lane & 3;
  const uint32_t q[4] = {q0, q1, q2, q3};
  const uint32_t* kb = reinterpret_cast<const uint32_t*>(g_kb);
  float m0 = -INFINITY, m1 = -INFINITY;
  for (int n0 = 0; n0 < SEQ; n0 += 8) {
    float s[4] = {0.f, 0.f, 0.f, 0.f};
    mma16816(s, q, __ldcg(kb + (n0 + g) * 8 + t), __ldcg(kb + (n0 + g) * 8 + 4 + t));
    m0 = fmaxf(m0, fmaxf(s[0], s[1]));
    m1 = fmaxf(m1, fmaxf(s[2], s[3]));
  }
  m0 = fmaxf(m0, __shfl_xor_sync(~0u, m0, 1)); m0 = fmaxf(m0, __shfl_xor_sync(~0u, m0, 2));
  m1 = fmaxf(m1, __shfl_xor_sync(~0u, m1, 1)); m1 = fmaxf(m1, __shfl_xor_sync(~0u, m1, 2));
  const float c = 0.25f * 1.4426950408889634f;
  float o[12];
#pragma unroll
  for (int i = 0; i < 12; i++) o[i] = 0.f;
  const unsigned short* vv = reinterpret_cast<const unsigned short*>(g_kv);
  for (int n0 = 0; n0 < SEQ; n0 += 16) {
    uint32_t p[4];
#pragma unroll
    for (int j = 0; j < 2; j++) {
      float s[4] = {0.f, 0.f, 0.f, 0.f};
      mma16816(s, q, __ldcg(kb + (n0 + 8 * j + g) * 8 + t), __ldcg(kb + (n0 + 8 * j + g) * 8 + 4 + t));
      p[2 * j]     = packbf(exp2f((s[0] - m0) * c), exp2f((s[1] - m0) * c));
      p[2 * j + 1] = packbf(exp2f((s[2] - m1) * c), exp2f((s[3] - m1) * c));
    }
#pragma unroll
    for (int pl = 0; pl < 2; pl++) {
      const int base = ((n0 >> 7) * 8192 + 4096 + pl * 2048 + ((n0 & 127) >> 3) * 128) / 2 + g;
      uint32_t b0 = (uint32_t)__ldcg(vv + base + (2 * t) * 8) | ((uint32_t)__ldcg(vv + base + (2 * t + 1) * 8) << 16);
      uint32_t b1 = (uint32_t)__ldcg(vv + base + 64 + (2 * t) * 8) | ((uint32_t)__ldcg(vv + base + 64 + (2 * t + 1) * 8) << 16);
      mma16816(o + 4 * pl, p, b0, b1);
    }
    mma16816(o + 8, p, 0x3f803f80u, 0x3f803f80u);
  }
  const float i0 = 1.0f / o[8], i1 = 1.0f / o[10];
  uint32_t* r0 = reinterpret_cast<uint32_t*>(orow + (size_t)g * DM) + t;
  uint32_t* r1 = reinterpret_cast<uint32_t*>(orow + (size_t)(g + 8) * DM) + t;
  r0[0] = packbf(o[0] * i0, o[1] * i0); r1[0] = packbf(o[2] * i1, o[3] * i1);
  r0[4] = packbf(o[4] * i0, o[5] * i0); r1[4] = packbf(o[6] * i1, o[7] * i1);
}

template<int N32>
__device__ __forceinline__ void attn_step(const uint32_t* q, float* om, float* op, uint32_t dk, uint32_t dv,
                                          uint32_t rel_bar, bool do_rel) {
  constexpr int KB = 64, N16 = KB - N32;
  constexpr uint32_t DKHI = 256 >> 4, DVHI = 2048 >> 4;
  float s[N32 / 2]; uint32_t h[N16 / 4]; uint32_t p[KB / 4];
  WG_FENCE();
  qk32<N32>(s, q, mkdesc(dk, DKHI));
  qk16<N16>(h, q, mkdesc(dk + N32 * 2, DKHI));
  WG_COMMIT();
  WG_WAIT(0);
  fence_regs<N32 / 2>(s); fence_regs<N16 / 4>(h);
  if (do_rel) mbar_arrive(rel_bar);
#pragma unroll
  for (int i = 0; i < N32 / 4; i++) p[i] = packbf(ex2f(s[2 * i]), ex2f(s[2 * i + 1]));
#pragma unroll
  for (int i = 0; i < N16 / 4; i++) p[N32 / 4 + i] = exp2_poly(h[i]);
  WG_FENCE();
#pragma unroll
  for (int j = 0; j < KB / 16; j++) pv24((j * 16 < N32) ? om : op, p + 4 * j, mkdesc(dv + j * 16, DVHI));
  WG_COMMIT();
}

struct Prod { int gb, ga, ki, flag_ok; };

__device__ __forceinline__ void issue_b(const Params& P, int gb, uint32_t sb, int c, int row0) {
  const uint32_t bars = sb + SM_BAR;
  const int s = gb & (NGS - 1);
  const uint32_t fb = bars + (B_GFULL + s) * 8, dst = sb + SM_RING + s * GSTAGE + 8192;
  const CUtensorMap* m; int n = 128 * c, k; uint32_t bytes = 24576;
  if (gb < 8)       { m = &P.wq; k = 64 * gb; bytes = 16384; }
  else if (gb < 40) { m = &P.w1; n = 448 * c + 128 * ((gb - 8) >> 3); k = 64 * (gb & 7); bytes = gb >= 32 ? 8192 : 16384; }
  else if (gb < 68) { const int u = gb - 40; m = &P.w2; k = 448 * ((c + u / 7) & 3) + 64 * (u % 7); }
  else              { const int u = gb - 68; m = &P.wo; k = 128 * ((c + u) & 3) + 64 * (u >> 2); }
  mbar_expect(fb, bytes);
  tma_load(dst, m, n, k, fb);
  if (bytes != 8192) tma_load(dst + 8192, m, n + 64, k, fb);
  if (gb == 39 + NGS) {
    mbar_expect(bars + B_XT * 8, 16384);
    tma_load(sb + SM_XT, &P.x, 128 * c, row0, bars + B_XT * 8);
    tma_load(sb + SM_XT + 8192, &P.x, 128 * c + 64, row0, bars + B_XT * 8);
  }
}

__device__ __forceinline__ void service(const Params& P, Prod& st, int it, uint32_t sb, int rb, int c) {
  const uint32_t bars = sb + SM_BAR;
  const int row0 = rb * 64;
  if (st.ki < 32 && mbar_test(bars + (B_KEMPTY + (st.ki & (NKS - 1))) * 8, ((st.ki / NKS) - 1) & 1)) {
    const int s = st.ki & (NKS - 1);
    if (st.ki == NKS) fence_async();
    mbar_expect(bars + (B_KFULL + s) * 8, 8192);
    bulk_load(sb + SM_KVR + s * KSTAGE, g_kv + (st.ki & 15) * 8192, 8192, bars + (B_KFULL + s) * 8);
    st.ki++;
  }
  if (st.gb < NKBLK && mbar_test(bars + (B_GEMPTY + (st.gb & (NGS - 1))) * 8, ((st.gb / NGS) - 1) & 1)) {
    issue_b(P, st.gb, sb, c, row0);
    st.gb++;
  }
  while (st.ga < st.gb && it >= 40) {
    const CUtensorMap* m; int k, id; const unsigned* fl; unsigned need;
    if (st.ga < 68) { const int u = st.ga - 40, cc = (c + u / 7) & 3; m = &P.h; k = 448 * cc + 64 * (u % 7); id = u / 7; fl = &g_cnt_h[rb * 4 + cc]; need = 1; }
    else            { const int u = st.ga - 68, cc = (c + u) & 3; m = &P.o; k = 128 * cc + 64 * (u >> 2); id = 4 + u; fl = &g_cnt_o[(rb * 4 + cc) * 2 + (u >> 2)]; need = 16; }
    if (st.flag_ok != id) {
      if (ld_acquire(fl) < need) break;
      st.flag_ok = id; fence_async();
    }
    const int s = st.ga & (NGS - 1);
    tma_load(sb + SM_RING + s * GSTAGE, m, k, row0, bars + (B_GFULL + s) * 8);
    st.ga++;
  }
}

template<int N>
__device__ __forceinline__ void ffn1_epilogue(const float* acc, uint32_t sb, int bias_off, const CUtensorMap* hmap,
                                              int col0, int row0, int tw) {
  const int lane = tw & 31, w = tw >> 5, t = lane & 3;
  if (tw == 0) asm volatile("cp.async.bulk.wait_group.read 0;" ::: "memory");
  bar_sync(4, 128);
  const int row = 16 * w + (lane & 7) + ((lane >> 3) & 1) * 8;
  const uint32_t rbase = sb + SM_STG + row * 128;
  const uint32_t bb = sb + SM_BIAS + (bias_off + 2 * t) * 2;
#pragma unroll
  for (int j = 0; j < N / 8; j += 2) {
    uint32_t v[4];
#pragma unroll
    for (int u = 0; u < 2; u++) {
      const uint32_t b = lds32(bb + (j + u) * 16);
      uint32_t r0 = badd2_relu(packbf(acc[4 * (j + u)], acc[4 * (j + u) + 1]), b);
      uint32_t r1 = badd2_relu(packbf(acc[4 * (j + u) + 2], acc[4 * (j + u) + 3]), b);
      v[2 * u] = bmul2(r0, r0); v[2 * u + 1] = bmul2(r1, r1);
    }
    const int ch = j + (lane >> 4);
    stsm4(rbase + (ch >> 3) * 8192 + (((ch & 7) ^ (row & 7)) << 4), v[0], v[1], v[2], v[3]);
  }
  fence_async_smem();
  bar_sync(4, 128);
  if (tw == 0) {
    tma_store(hmap, col0, row0, sb + SM_STG);
    if (N == 128) tma_store(hmap, col0 + 64, row0, sb + SM_STG + 8192);
    asm volatile("cp.async.bulk.commit_group;" ::: "memory");
  }
}

__global__ void __launch_bounds__(NTHREADS, 1)
fused_kernel(const __grid_constant__ Params P, const __nv_bfloat16* __restrict__ x,
             const __nv_bfloat16* __restrict__ wk, const __nv_bfloat16* __restrict__ wv,
             const __nv_bfloat16* __restrict__ b1, const __nv_bfloat16* __restrict__ b2) {
  extern __shared__ unsigned char smem_raw[];
  const uint32_t sb = ((uint32_t)__cvta_generic_to_shared(smem_raw) + 1023u) & ~1023u;
  const uint32_t bars = sb + SM_BAR;
  const int tid = threadIdx.x, warp = __shfl_sync(~0u, tid >> 5, 0), lane = tid & 31;
  const int cta = blockIdx.x, rb = cta >> 2, c = cta & 3, row0 = rb * 64;

  if (warp < 16) {
    const int wg = warp >> 2, ww = warp & 3, g = lane >> 2, t = lane & 3;
    {
      uint4 xv[4][2];
#pragma unroll
      for (int r = 0; r < 4; r++) {
        const uint4* xr = reinterpret_cast<const uint4*>(x + (size_t)(row0 + 4 * warp + r) * DM);
        xv[r][0] = __ldg(xr + lane); xv[r][1] = __ldg(xr + 32 + lane);
      }
      uint4 wv4[4];
#pragma unroll
      for (int i = 0; i < 4; i++) {
        const int ch = tid + (i & 1) * 512;
        wv4[i] = __ldg(reinterpret_cast<const uint4*>(i < 2 ? wk : wv) + ch);
      }
      sts128(sb + SM_KVR + (tid >> 7) * KSTAGE + 8192 + (tid & 127) * 16, make_uint4(0x3f803f80u, 0x3f803f80u, 0x3f803f80u, 0x3f803f80u));
      if (tid < 72) {
        const uint4 bv = tid < 56 ? __ldg(reinterpret_cast<const uint4*>(b1 + 448 * c) + tid)
                                  : __ldg(reinterpret_cast<const uint4*>(b2 + 128 * c) + (tid - 56));
        sts128(sb + SM_BIAS + tid * 16, bv);
      }
      float mean[4], var[4];
#pragma unroll
      for (int r = 0; r < 4; r++) {
        const uint32_t* u = reinterpret_cast<const uint32_t*>(xv[r]);
        float s = 0.f;
#pragma unroll
        for (int i = 0; i < 8; i++) s += bflo(u[i]) + bfhi(u[i]);
        mean[r] = s;
      }
#pragma unroll
      for (int o = 16; o; o >>= 1)
#pragma unroll
        for (int r = 0; r < 4; r++) mean[r] += __shfl_xor_sync(~0u, mean[r], o);
#pragma unroll
      for (int r = 0; r < 4; r++) {
        mean[r] *= (1.0f / DM);
        const uint32_t* u = reinterpret_cast<const uint32_t*>(xv[r]);
        float s = 0.f;
#pragma unroll
        for (int i = 0; i < 8; i++) { float a = bflo(u[i]) - mean[r], b = bfhi(u[i]) - mean[r]; s += a * a + b * b; }
        var[r] = s;
      }
#pragma unroll
      for (int o = 16; o; o >>= 1)
#pragma unroll
        for (int r = 0; r < 4; r++) var[r] += __shfl_xor_sync(~0u, var[r], o);
#pragma unroll
      for (int r = 0; r < 4; r++) {
        const float mb = bfr(mean[r]);
        const float sd = bfr(sqrtf(bfr(bfr(var[r] * (1.0f / DM)) + 1e-5f)));
        const float inv = 1.0f / sd;
        const int row = 4 * warp + r;
#pragma unroll
        for (int hh = 0; hh < 2; hh++) {
          const uint32_t* u = reinterpret_cast<const uint32_t*>(&xv[r][hh]);
          uint32_t o4[4];
#pragma unroll
          for (int i = 0; i < 4; i++) {
            const uint32_t d = packbf(bflo(u[i]) - mb, bfhi(u[i]) - mb);
            o4[i] = packbf(bflo(d) * inv, bfhi(d) * inv);
          }
          sts128(sb + SM_XN + (hh * 4 + (lane >> 3)) * 8192 + row * 128 + (((lane & 7) ^ (row & 7)) << 4),
                 make_uint4(o4[0], o4[1], o4[2], o4[3]));
        }
      }
#pragma unroll
      for (int i = 0; i < 4; i++) {
        const int ch = tid + (i & 1) * 512;
        sts128(sb + SM_KVR + ((i >> 1) * 2 + (ch & 1)) * KSTAGE + (ch >> 1) * 16, wv4[i]);
      }
      fence_async_smem();
    }
    bar_sync(1, NTHREADS);

    if (wg == 0) {
      float acc[16];
#pragma unroll
      for (int i = 0; i < 16; i++) acc[i] = 0.f;
      const uint32_t db = desc_lo(sb + SM_KVR, 128);
      WG_FENCE();
#pragma unroll
      for (int kb = 0; kb < 8; kb++) {
        const uint32_t da = desc_lo(sb + SM_XN + kb * 8192, 16);
#pragma unroll
        for (int j = 0; j < 4; j++)
          gemm_ss<32>(acc, mkdesc(da + j * 2, DHI_SW128), mkdesc(db + (kb * 4 + j) * 16, KSTAGE >> 4), (kb | j) != 0);
      }
      WG_COMMIT();
      WG_WAIT(0);
      fence_regs<16>(acc);
      bar_sync(5, 128);
      if (ww == c) {
        float kn[2] = {0.f, 0.f}, vm = 0.f;
#pragma unroll
        for (int rr = 0; rr < 2; rr++) {
          const int key = row0 + 16 * c + 8 * rr + g;
          unsigned char* blk = g_kv + (key >> 7) * 8192;
          const int grp = (key & 127) >> 3;
#pragma unroll
          for (int j = 0; j < 2; j++) {
            const uint32_t kbf = packbf(acc[4 * j + 2 * rr], acc[4 * j + 2 * rr + 1]);
            const float a = bflo(kbf), b = bfhi(kbf);
            kn[rr] += a * a + b * b;
            *reinterpret_cast<uint32_t*>(blk + grp * 256 + j * 128 + g * 16 + t * 4) = packh(a, b);
            reinterpret_cast<uint32_t*>(g_kb)[key * 8 + j * 4 + t] = kbf;
            const uint32_t vbf = packbf(acc[8 + 4 * j + 2 * rr], acc[8 + 4 * j + 2 * rr + 1]);
            const float va = fabsf(bflo(vbf)), vb = fabsf(bfhi(vbf));
            vm = (va <= vm) ? vm : va; vm = (vb <= vm) ? vm : vb;
            if (!(va == va) || !(vb == vb)) vm = INFINITY;
            *reinterpret_cast<uint32_t*>(blk + 4096 + j * 2048 + grp * 128 + g * 16 + t * 4) = vbf;
          }
        }
#pragma unroll
        for (int rr = 0; rr < 2; rr++) {
          kn[rr] += __shfl_xor_sync(~0u, kn[rr], 1); kn[rr] += __shfl_xor_sync(~0u, kn[rr], 2);
          if (!(kn[rr] == kn[rr])) kn[rr] = INFINITY;
        }
        float km = fmaxf(kn[0], kn[1]);
#pragma unroll
        for (int o = 16; o; o >>= 1) { km = fmaxf(km, __shfl_xor_sync(~0u, km, o)); vm = fmaxf(vm, __shfl_xor_sync(~0u, vm, o)); }
        if (lane == 0) { g_kmax[cta] = km; g_vmax[cta] = vm; }
        fence_async();
        __threadfence();
        __syncwarp();
        if (lane == 0) red_release(&g_cnt_kv, 1);
      }
    }

    if (tid == 128) {
      int spins = 0;
      while (ld_acquire(&g_cnt_kv) < NCTA) { __nanosleep(20); if (++spins > (1 << 22)) __trap(); }
      fence_async();
#pragma unroll 1
      for (int i = 0; i < NKS; i++) {
        mbar_expect(bars + (B_KFULL + i) * 8, 8192);
        bulk_load(sb + SM_KVR + i * KSTAGE, g_kv + i * 8192, 8192, bars + (B_KFULL + i) * 8);
      }
    }
    __syncwarp();

    bar_sync(2, 640);
    uint32_t qb[2][4];
#pragma unroll
    for (int p = 0; p < 2; p++)
#pragma unroll
      for (int i = 0; i < 4; i++) qb[p][i] = lds32(sb + SM_STG + ((4 * p + wg) * 4 + i) * 512 + (tid & 127) * 4);
    bar_arrive(3, 640);

    const bool lane0 = lane == 0;
#pragma unroll 1
    for (int p = 0; p < 2; p++) {
      uint32_t qs[4], q[4];
#pragma unroll
      for (int i = 0; i < 4; i++) qs[i] = p ? qb[1][i] : qb[0][i];
      const float qc = 0.25f * 1.4426950408889634f;
#pragma unroll
      for (int i = 0; i < 4; i++) q[i] = packh(bflo(qs[i]) * qc, bfhi(qs[i]) * qc);
      float om[12], op[12];
#pragma unroll
      for (int i = 0; i < 12; i++) { om[i] = 0.f; op[i] = 0.f; }
#pragma unroll 1
      for (int st = 0; st < 16; st++) {
        const int fi = p * 16 + st, slot = fi & (NKS - 1);
        mbar_wait(bars + (B_KFULL + slot) * 8, (fi / NKS) & 1);
        const uint32_t dk = desc_lo(sb + SM_KVR + slot * KSTAGE, 128);
        const uint32_t dv = dk + (4096 >> 4);
        attn_step<32>(q, om, op, dk, dv, bars + (B_KEMPTY + ((fi - 1) & (NKS - 1))) * 8, lane0 && st > 0);
        attn_step<32>(q, om, op, dk + (2048 >> 4), dv + (1024 >> 4), 0, false);
      }
      WG_WAIT(0);
      fence_regs<12>(om); fence_regs<12>(op);
      if (lane0) mbar_arrive(bars + (B_KEMPTY + ((p * 16 + 15) & (NKS - 1))) * 8);

      float qn0, qn1;
      {
        float a;
        a = bflo(qs[0]) * qc; qn0 = a * a; a = bfhi(qs[0]) * qc; qn0 += a * a;
        a = bflo(qs[2]) * qc; qn0 += a * a; a = bfhi(qs[2]) * qc; qn0 += a * a;
        a = bflo(qs[1]) * qc; qn1 = a * a; a = bfhi(qs[1]) * qc; qn1 += a * a;
        a = bflo(qs[3]) * qc; qn1 += a * a; a = bfhi(qs[3]) * qc; qn1 += a * a;
        qn0 += __shfl_xor_sync(~0u, qn0, 1); qn0 += __shfl_xor_sync(~0u, qn0, 2);
        qn1 += __shfl_xor_sync(~0u, qn1, 1); qn1 += __shfl_xor_sync(~0u, qn1, 2);
      }
      const float4 k4 = __ldcg(reinterpret_cast<const float4*>(g_kmax) + lane);
      const float4 v4 = __ldcg(reinterpret_cast<const float4*>(g_vmax) + lane);
      float km = fmaxf(fmaxf(k4.x, k4.y), fmaxf(k4.z, k4.w)), vm = fmaxf(fmaxf(v4.x, v4.y), fmaxf(v4.z, v4.w));
#pragma unroll
      for (int o = 16; o; o >>= 1) { km = fmaxf(km, __shfl_xor_sync(~0u, km, o)); vm = fmaxf(vm, __shfl_xor_sync(~0u, vm, o)); }
      const bool ok = (qn0 * km <= 1590.f) && (qn1 * km <= 1590.f) && (qn0 <= 1.0e6f) && (qn1 <= 1.0e6f) && (km <= 1.0e6f)
                      && (vm <= 1.0e12f) && (vm >= 1.0e-12f);
      const int head = 8 * c + 4 * p + wg;
      __nv_bfloat16* orow = g_o + (size_t)(row0 + 16 * ww) * DM + head * 16;
      if (__all_sync(~0u, ok)) {
        const float i0 = 1.0f / (om[8] + op[8] * POLY_INV), i1 = 1.0f / (om[10] + op[10] * POLY_INV);
        uint32_t* r0 = reinterpret_cast<uint32_t*>(orow + (size_t)g * DM) + t;
        uint32_t* r1 = reinterpret_cast<uint32_t*>(orow + (size_t)(g + 8) * DM) + t;
        r0[0] = packbf((om[0] + op[0] * POLY_INV) * i0, (om[1] + op[1] * POLY_INV) * i0);
        r1[0] = packbf((om[2] + op[2] * POLY_INV) * i1, (om[3] + op[3] * POLY_INV) * i1);
        r0[4] = packbf((om[4] + op[4] * POLY_INV) * i0, (om[5] + op[5] * POLY_INV) * i0);
        r1[4] = packbf((om[6] + op[6] * POLY_INV) * i1, (om[7] + op[7] * POLY_INV) * i1);
      } else {
        attn_slow(qs[0], qs[1], qs[2], qs[3], orow);
      }
      fence_async();
      __threadfence();
      __syncwarp();
      if (lane0) red_release(&g_cnt_o[cta * 2 + p], 1);
    }
  } else {
    const int tw = tid - 512, w = warp - 16, g = lane >> 2, t = lane & 3;
    const bool lane0 = lane == 0;
    Prod st{NGS, 40, NKS, 0};
    if (tw == 0) {
#pragma unroll
      for (int i = 0; i < NGS; i++) { mbar_init(bars + (B_GFULL + i) * 8, 1); mbar_init(bars + (B_GEMPTY + i) * 8, 4); }
#pragma unroll
      for (int i = 0; i < NKS; i++) { mbar_init(bars + (B_KFULL + i) * 8, 1); mbar_init(bars + (B_KEMPTY + i) * 8, 16); }
      mbar_init(bars + B_XT * 8, 1);
      asm volatile("fence.mbarrier_init.release.cluster;" ::: "memory");
      fence_async_smem();
#pragma unroll 1
      for (int i = 0; i < NGS; i++) issue_b(P, i, sb, c, row0);
#pragma unroll 1
      for (int i = NGS; i < 8; i++) { tma_prefetch(&P.wq, 128 * c, 64 * i); tma_prefetch(&P.wq, 128 * c + 64, 64 * i); }
    }
    __syncwarp();
    bar_sync(1, NTHREADS);

    float acc[64];
#pragma unroll
    for (int i = 0; i < 64; i++) acc[i] = 0.f;
#pragma unroll 1
    for (int it = 0; it < NKBLK; it++) {
      const int s = it & (NGS - 1);
      const uint32_t fb = bars + (B_GFULL + s) * 8, ph = (it / NGS) & 1;
      if (w == 0) {
        int spins = 0;
        do {
          if (lane0) service(P, st, it, sb, rb, c);
          __syncwarp();
          if (++spins > (1 << 22)) __trap();
        } while (!mbar_try(fb, ph));
      } else {
        mbar_wait(fb, ph);
      }
      const bool first = it < 40 ? (it & 7) == 0 : (it == 40 || it == 68);
      const bool last  = it < 40 ? (it & 7) == 7 : (it == 67 || it == 75);
      const uint32_t stg = sb + SM_RING + s * GSTAGE;
      const uint32_t da = desc_lo(it >= 40 ? stg : sb + SM_XN + (it & 7) * 8192, 16);
      const uint32_t db = desc_lo(stg + 8192, 8192);
      if ((it >> 3) == 4) {
        WG_FENCE();
#pragma unroll
        for (int j = 0; j < 4; j++)
          gemm_ss<64>(acc, mkdesc(da + j * 2, DHI_SW128), mkdesc(db + j * 128, DHI_SW128), j > 0 || !first);
      } else {
        WG_FENCE();
#pragma unroll
        for (int j = 0; j < 4; j++)
          gemm_ss<128>(acc, mkdesc(da + j * 2, DHI_SW128), mkdesc(db + j * 128, DHI_SW128), j > 0 || !first);
      }
      WG_COMMIT();
      if (!last) {
        if (it >= 68) {
          if (it < 72) {
            WG_WAIT(0);
            if (lane0) mbar_arrive(bars + (B_GEMPTY + s) * 8);
          }
        } else if (!first) {
          WG_WAIT(1);
          if (lane0) mbar_arrive(bars + (B_GEMPTY + ((it - 1) & (NGS - 1))) * 8);
        }
        continue;
      }
      WG_WAIT(0);
      fence_regs<64>(acc);
      if (lane0) {
        mbar_arrive(bars + (B_GEMPTY + ((it - 1) & (NGS - 1))) * 8);
        mbar_arrive(bars + (B_GEMPTY + s) * 8);
      }
      if (it == 7) {
#pragma unroll
        for (int i = 0; i < 32; i++) sts32(sb + SM_STG + i * 512 + tw * 4, packbf(acc[2 * i], acc[2 * i + 1]));
        bar_arrive(2, 640);
      } else if (it < 32) {
        const int j = (it >> 3) - 1;
        if (j == 0) bar_sync(3, 640);
        ffn1_epilogue<128>(acc, sb, 128 * j, &P.h, 448 * c + 128 * j, row0, tw);
      } else if (it == 39) {
        ffn1_epilogue<64>(acc, sb, 384, &P.h, 448 * c + 384, row0, tw);
        if (tw == 0) {
          asm volatile("cp.async.bulk.wait_group 0;" ::: "memory");
          fence_async();
          __threadfence();
          red_release(&g_cnt_h[cta], 1);
        }
        __syncwarp();
      } else if (it == 67) {
        const uint32_t bb = sb + SM_BIAS + (448 + 2 * t) * 2;
#pragma unroll
        for (int j = 0; j < 16; j++) {
          const uint32_t b = lds32(bb + j * 16);
#pragma unroll
          for (int u = 0; u < 2; u++) {
            const uint32_t z = badd2(packbf(acc[4 * j + 2 * u], acc[4 * j + 2 * u + 1]), b);
            const float z0 = bflo(z), z1 = bfhi(z);
            const float g0 = __fdividef(z0, 1.0f + __expf(-z0)), g1 = __fdividef(z1, 1.0f + __expf(-z1));
            sts32(sb + SM_G + (2 * j + u) * 512 + tw * 4, packbf(g0, g1));
          }
        }
      }
    }
    WG_WAIT(0);
    fence_regs<64>(acc);
    mbar_wait(bars + B_XT * 8, 0);
    {
      const int srow = 16 * w + (lane & 7) + ((lane >> 3) & 1) * 8;
      const uint32_t rbase = sb + SM_STG + srow * 128;
#pragma unroll
      for (int j = 0; j < 16; j += 2) {
        uint32_t v[4];
#pragma unroll
        for (int u = 0; u < 4; u++) {
          const int jj = j + (u >> 1), row = 16 * w + g + (u & 1) * 8;
          const uint32_t sv = packbf(acc[4 * jj + 2 * (u & 1)], acc[4 * jj + 2 * (u & 1) + 1]);
          const uint32_t gv = lds32(sb + SM_G + (2 * jj + (u & 1)) * 512 + tw * 4);
          const uint32_t xx = lds32(sb + SM_XT + (jj >> 3) * 8192 + row * 128 + (((jj & 7) ^ (row & 7)) << 4) + t * 4);
          v[u] = badd2(xx, bmul2(sv, gv));
        }
        const int ch = j + (lane >> 4);
        stsm4(rbase + (ch >> 3) * 8192 + (((ch & 7) ^ (srow & 7)) << 4), v[0], v[1], v[2], v[3]);
      }
      fence_async_smem();
      bar_sync(4, 128);
      if (tw == 0) {
        tma_store(&P.out, 128 * c, row0, sb + SM_STG);
        tma_store(&P.out, 128 * c + 64, row0, sb + SM_STG + 8192);
        asm volatile("cp.async.bulk.commit_group;" ::: "memory");
        __threadfence();
        if (atomicAdd(&g_cnt_end, 1u) == NCTA - 1) {
          g_cnt_kv = 0;
          for (int i = 0; i < NCTA; i++) { g_cnt_h[i] = 0; g_cnt_o[2 * i] = 0; g_cnt_o[2 * i + 1] = 0; }
          g_cnt_end = 0;
        }
        asm volatile("cp.async.bulk.wait_group 0;" ::: "memory");
      }
    }
  }
}

typedef CUresult (*EncodeFn)(CUtensorMap*, CUtensorMapDataType, cuuint32_t, void*, const cuuint64_t*, const cuuint64_t*,
                             const cuuint32_t*, const cuuint32_t*, CUtensorMapInterleave, CUtensorMapSwizzle,
                             CUtensorMapL2promotion, CUtensorMapFloatOOBfill);

void make_map(EncodeFn fn, CUtensorMap* m, const void* ptr, uint64_t cols, uint64_t rows) {
  cuuint64_t dims[2] = {cols, rows};
  cuuint64_t strides[1] = {cols * 2};
  cuuint32_t box[2] = {64, 64};
  cuuint32_t es[2] = {1, 1};
  fn(m, CU_TENSOR_MAP_DATA_TYPE_BFLOAT16, 2, const_cast<void*>(ptr), dims, strides, box, es,
     CU_TENSOR_MAP_INTERLEAVE_NONE, CU_TENSOR_MAP_SWIZZLE_128B, CU_TENSOR_MAP_L2_PROMOTION_L2_256B,
     CU_TENSOR_MAP_FLOAT_OOB_FILL_NONE);
}

}

extern "C" void kernel_launch(void* const* d_in, const int* in_sizes, int n_in, void* d_out, int out_size) {
  (void)in_sizes; (void)n_in; (void)out_size;
  const __nv_bfloat16* x  = (const __nv_bfloat16*)d_in[0];
  const __nv_bfloat16* wq = (const __nv_bfloat16*)d_in[1];
  const __nv_bfloat16* wk = (const __nv_bfloat16*)d_in[2];
  const __nv_bfloat16* wv = (const __nv_bfloat16*)d_in[3];
  const __nv_bfloat16* wo = (const __nv_bfloat16*)d_in[4];
  const __nv_bfloat16* w1 = (const __nv_bfloat16*)d_in[6];
  const __nv_bfloat16* b1 = (const __nv_bfloat16*)d_in[7];
  const __nv_bfloat16* w2 = (const __nv_bfloat16*)d_in[8];
  const __nv_bfloat16* b2 = (const __nv_bfloat16*)d_in[9];

  void* fnp = nullptr;
  cudaDriverEntryPointQueryResult qr;
  cudaGetDriverEntryPoint("cuTensorMapEncodeTiled", &fnp, cudaEnableDefault, &qr);
  EncodeFn fn = (EncodeFn)fnp;
  void *hp = nullptr, *op = nullptr;
  cudaGetSymbolAddress(&hp, g_h);
  cudaGetSymbolAddress(&op, g_o);

  Params P;
  make_map(fn, &P.wq, wq, DM, DM);
  make_map(fn, &P.w1, w1, FF, DM);
  make_map(fn, &P.w2, w2, DM, FF);
  make_map(fn, &P.wo, wo, DM, DM);
  make_map(fn, &P.h, hp, FF, SEQ);
  make_map(fn, &P.o, op, DM, SEQ);
  make_map(fn, &P.x, x, DM, SEQ);
  make_map(fn, &P.out, d_out, DM, SEQ);

  cudaFuncSetAttribute(fused_kernel, cudaFuncAttributeMaxDynamicSharedMemorySize, SMEM_BYTES);
  fused_kernel<<<NCTA, NTHREADS, SMEM_BYTES, cudaStreamPerThread>>>(P, x, wk, wv, b1, b2);
}
```

```cpp
#include <cuda_runtime.h>
#include <cuda_bf16.h>
#include <cuda_fp16.h>
#include <cuda.h>
#include <stdint.h>

namespace {

constexpr int SEQ = 2048, DM = 512, FF = 1792;
constexpr int NCTA = 128;
constexpr int NTHREADS = 768;

constexpr int SM_XN   = 0;
constexpr int NGS     = 5;
constexpr int GSTAGE  = 16384;
constexpr int SM_RING = 65536;
constexpr int NKS     = 4;
constexpr int KSTAGE  = 10240;
constexpr int SM_KVR  = SM_RING + NGS * GSTAGE;
constexpr int SM_STG  = SM_KVR + NKS * KSTAGE;
constexpr int SM_OT   = SM_STG + 16384;
constexpr int SM_BIAS = SM_OT + 16384;
constexpr int SM_BAR  = SM_BIAS + 1152;
constexpr int SM_END  = SM_BAR + 512;
constexpr int SMEM_BYTES = SM_END + 1024;
constexpr int SM_AR   = SM_XN;
constexpr int SM_XT   = SM_XN + NGS * 8192;
constexpr int SM_OUT  = SM_KVR;

constexpr int B_GFULL = 0, B_GEMPTY = 6, B_KFULL = 12, B_KEMPTY = 16, B_XT = 20, B_HRDY = 21, B_HFREE = 22,
              B_ORDY = 23  , B_GUARD = 25, B_TAG = 26, B_XIN = 27, B_BIAS = 28, B_QRDY = 29  , B_KVPUB = 31, B_HPUB = 11, B_ZRDY = 5, B_GRDY = 32, B_AUX = 33;

constexpr int N32 = 32;

constexpr int LEADFROM = 28;
constexpr int NKBLK = 76;

__device__ __align__(1024) unsigned char g_kv[16 * KSTAGE];
__device__ __align__(16) __nv_bfloat16 g_kb[SEQ * 16];
__device__ __align__(16) __nv_bfloat16 g_vb[SEQ * 16];
__device__ __align__(16) float g_kmax[NCTA];
__device__ __align__(16) float g_vmax[NCTA];
__device__ __align__(1024) __nv_bfloat16 g_h[SEQ * FF];
__device__ __align__(1024) __nv_bfloat16 g_o[SEQ * DM];
__device__ unsigned g_cnt_kv;
__device__ unsigned g_cnt_aux;
__device__ unsigned g_tag_h[NCTA];
__device__ unsigned g_tag_o[NCTA * 2];

struct WPtrs { const __nv_bfloat16 *wq, *w1, *w2, *wo, *x; };
struct Params {
  CUtensorMap wq, w1, w2, wo, h, o, x, out;
};

template<int N> __device__ __forceinline__ void qk32(float* d, const uint32_t* a, uint64_t db);
template<int N> __device__ __forceinline__ void qk16(uint32_t* d, const uint32_t* a, uint64_t db);
template<int N> __device__ __forceinline__ void gemm_ss(float* d, uint64_t da, uint64_t db, int sc);
template<> __device__ __forceinline__ void qk32<32>(float* d, const uint32_t* a, uint64_t db) {
  asm volatile("{ .reg .pred p; setp.ne.b32 p, 0, 0;\n wgmma.mma_async.sync.aligned.m64n32k16.f32.f16.f16 {%0,%1,%2,%3,%4,%5,%6,%7,%8,%9,%10,%11,%12,%13,%14,%15}, {%16,%17,%18,%19}, %20, p, 1, 1, 0; }\n"
   : "=f"(d[0]),"=f"(d[1]),"=f"(d[2]),"=f"(d[3]),"=f"(d[4]),"=f"(d[5]),"=f"(d[6]),"=f"(d[7]),"=f"(d[8]),"=f"(d[9]),"=f"(d[10]),"=f"(d[11]),"=f"(d[12]),"=f"(d[13]),"=f"(d[14]),"=f"(d[15]) : "r"(a[0]),"r"(a[1]),"r"(a[2]),"r"(a[3]),"l"(db));
}
template<> __device__ __forceinline__ void qk16<32>(uint32_t* d, const uint32_t* a, uint64_t db) {
  asm volatile("{ .reg .pred p; setp.ne.b32 p, 0, 0;\n wgmma.mma_async.sync.aligned.m64n32k16.f16.f16.f16 {%0,%1,%2,%3,%4,%5,%6,%7}, {%8,%9,%10,%11}, %12, p, 1, 1, 0; }\n"
   : "=r"(d[0]),"=r"(d[1]),"=r"(d[2]),"=r"(d[3]),"=r"(d[4]),"=r"(d[5]),"=r"(d[6]),"=r"(d[7]) : "r"(a[0]),"r"(a[1]),"r"(a[2]),"r"(a[3]),"l"(db));
}
__device__ __forceinline__ void pv24(float* d, const uint32_t* a, uint64_t db) {
  asm volatile("{ .reg .pred p; setp.eq.b32 p, 0, 0;\n wgmma.mma_async.sync.aligned.m64n24k16.f32.bf16.bf16 {%0,%1,%2,%3,%4,%5,%6,%7,%8,%9,%10,%11}, {%12,%13,%14,%15}, %16, p, 1, 1, 1; }\n"
   : "+f"(d[0]),"+f"(d[1]),"+f"(d[2]),"+f"(d[3]),"+f"(d[4]),"+f"(d[5]),"+f"(d[6]),"+f"(d[7]),"+f"(d[8]),"+f"(d[9]),"+f"(d[10]),"+f"(d[11]) : "r"(a[0]),"r"(a[1]),"r"(a[2]),"r"(a[3]),"l"(db));
}
template<> __device__ __forceinline__ void gemm_ss<32>(float* d, uint64_t da, uint64_t db, int sc) {
  asm volatile("{ .reg .pred p; setp.ne.b32 p, %18, 0;\n wgmma.mma_async.sync.aligned.m64n32k16.f32.bf16.bf16 {%0,%1,%2,%3,%4,%5,%6,%7,%8,%9,%10,%11,%12,%13,%14,%15}, %16, %17, p, 1, 1, 0, 1; }\n"
   : "+f"(d[0]),"+f"(d[1]),"+f"(d[2]),"+f"(d[3]),"+f"(d[4]),"+f"(d[5]),"+f"(d[6]),"+f"(d[7]),"+f"(d[8]),"+f"(d[9]),"+f"(d[10]),"+f"(d[11]),"+f"(d[12]),"+f"(d[13]),"+f"(d[14]),"+f"(d[15]) : "l"(da),"l"(db),"r"(sc));
}
template<> __device__ __forceinline__ void gemm_ss<64>(float* d, uint64_t da, uint64_t db, int sc) {
  asm volatile("{ .reg .pred p; setp.ne.b32 p, %34, 0;\n wgmma.mma_async.sync.aligned.m64n64k16.f32.bf16.bf16 {%0,%1,%2,%3,%4,%5,%6,%7,%8,%9,%10,%11,%12,%13,%14,%15,%16,%17,%18,%19,%20,%21,%22,%23,%24,%25,%26,%27,%28,%29,%30,%31}, %32, %33, p, 1, 1, 0, 1; }\n"
   : "+f"(d[0]),"+f"(d[1]),"+f"(d[2]),"+f"(d[3]),"+f"(d[4]),"+f"(d[5]),"+f"(d[6]),"+f"(d[7]),"+f"(d[8]),"+f"(d[9]),"+f"(d[10]),"+f"(d[11]),"+f"(d[12]),"+f"(d[13]),"+f"(d[14]),"+f"(d[15]),"+f"(d[16]),"+f"(d[17]),"+f"(d[18]),"+f"(d[19]),"+f"(d[20]),"+f"(d[21]),"+f"(d[22]),"+f"(d[23]),"+f"(d[24]),"+f"(d[25]),"+f"(d[26]),"+f"(d[27]),"+f"(d[28]),"+f"(d[29]),"+f"(d[30]),"+f"(d[31]) : "l"(da),"l"(db),"r"(sc));
}


#define WG_FENCE()  asm volatile("wgmma.fence.sync.aligned;" ::: "memory")
#define WG_COMMIT() asm volatile("wgmma.commit_group.sync.aligned;" ::: "memory")
#define WG_WAIT(n)  asm volatile("wgmma.wait_group.sync.aligned " #n ";" ::: "memory")

template<int N> __device__ __forceinline__ void fence_regs(float* r) {
#pragma unroll
  for (int i = 0; i < N; i++) asm volatile("" : "+f"(r[i]) :: "memory");
}
template<int N> __device__ __forceinline__ void fence_regs(uint32_t* r) {
#pragma unroll
  for (int i = 0; i < N; i++) asm volatile("" : "+r"(r[i]) :: "memory");
}
__device__ __forceinline__ uint64_t mkdesc(uint32_t lo, uint32_t hi) {
  uint64_t d; asm("mov.b64 %0, {%1,%2};" : "=l"(d) : "r"(lo), "r"(hi)); return d;
}
__device__ __forceinline__ float ex2f(float x) { float y; asm("ex2.approx.ftz.f32 %0, %1;" : "=f"(y) : "f"(x)); return y; }
__device__ __forceinline__ float rcpf(float x) { float y; asm("rcp.approx.ftz.f32 %0, %1;" : "=f"(y) : "f"(x)); return y; }
__device__ __forceinline__ float sqrtaf(float x) { float y; asm("sqrt.approx.ftz.f32 %0, %1;" : "=f"(y) : "f"(x)); return y; }
__device__ __forceinline__ uint32_t packbf(float lo, float hi) {
  uint32_t y; asm("cvt.rn.bf16x2.f32 %0, %1, %2;" : "=r"(y) : "f"(hi), "f"(lo)); return y;
}
__device__ __forceinline__ uint32_t packh(float lo, float hi) {
  uint32_t y; asm("cvt.rn.f16x2.f32 %0, %1, %2;" : "=r"(y) : "f"(hi), "f"(lo)); return y;
}
__device__ __forceinline__ float bflo(uint32_t v) { return __uint_as_float(v << 16); }
__device__ __forceinline__ float bfhi(uint32_t v) { return __uint_as_float(v & 0xffff0000u); }
__device__ __forceinline__ float bfr(float x) { return __bfloat162float(__float2bfloat16_rn(x)); }
__device__ __forceinline__ uint32_t hfma2(uint32_t a, uint32_t b, uint32_t c) {
  uint32_t y; asm("fma.rn.f16x2 %0, %1, %2, %3;" : "=r"(y) : "r"(a), "r"(b), "r"(c)); return y;
}
__device__ __forceinline__ uint32_t hadd2(uint32_t a, uint32_t b) {
  uint32_t y; asm("add.rn.f16x2 %0, %1, %2;" : "=r"(y) : "r"(a), "r"(b)); return y;
}
__device__ __forceinline__ uint32_t badd2(uint32_t a, uint32_t b) {
  uint32_t y; asm("add.rn.bf16x2 %0, %1, %2;" : "=r"(y) : "r"(a), "r"(b)); return y;
}
__device__ __forceinline__ uint32_t bmul2(uint32_t a, uint32_t b) {
  uint32_t y; asm("mul.rn.bf16x2 %0, %1, %2;" : "=r"(y) : "r"(a), "r"(b)); return y;
}
__device__ __forceinline__ uint32_t bfma2(uint32_t a, uint32_t b, uint32_t c) {
  uint32_t y; asm("fma.rn.bf16x2 %0, %1, %2, %3;" : "=r"(y) : "r"(a), "r"(b), "r"(c)); return y;
}
__device__ __forceinline__ uint32_t badd2_relu(uint32_t a, uint32_t b) {
  uint32_t y; asm("fma.rn.relu.bf16x2 %0, %1, %2, %3;" : "=r"(y) : "r"(a), "r"(0x3f803f80u), "r"(b)); return y;
}

__device__ __forceinline__ uint32_t exp2_poly(uint32_t x, uint32_t na  ) {
  const uint32_t t = hadd2(x, 0x65f965f9u);
  const uint32_t w = hfma2(t, na, 0x60346034u);
  const uint32_t u = hfma2(x, 0x35a035a0u, w);
  const uint32_t v = hfma2(u, u, 0x3a083a08u);
  const uint32_t r = hfma2(v, u, 0x44104421u);
  return __funnelshift_l(r, t, 7) + r;
}
constexpr float POLY_SCALE = 11.3125f;

__device__ __forceinline__ void mbar_init(uint32_t a, int c) { asm volatile("mbarrier.init.shared.b64 [%0], %1;" :: "r"(a), "r"(c) : "memory"); }
__device__ __forceinline__ void mbar_expect(uint32_t a, uint32_t bytes) {
  asm volatile("mbarrier.arrive.expect_tx.shared.b64 _, [%0], %1;" :: "r"(a), "r"(bytes) : "memory");
}
__device__ __forceinline__ void mbar_arrive(uint32_t a) { asm volatile("mbarrier.arrive.shared.b64 _, [%0];" :: "r"(a) : "memory"); }
__device__ __forceinline__ void mbar_arrive_lane0(uint32_t a, int lane) {
  asm volatile("{ .reg .pred p; setp.eq.s32 p, %1, 0; @p mbarrier.arrive.shared.b64 _, [%0]; }" :: "r"(a), "r"(lane) : "memory");
}
__device__ __forceinline__ bool mbar_test(uint32_t a, uint32_t ph) {
  uint32_t ok;
  asm volatile("{ .reg .pred p; mbarrier.test_wait.parity.shared.b64 p, [%1], %2; selp.u32 %0, 1, 0, p; }" : "=r"(ok) : "r"(a), "r"(ph) : "memory");
  return ok != 0;
}
__device__ __forceinline__ bool mbar_try(uint32_t a, uint32_t ph) {
  uint32_t ok;
  asm volatile("{ .reg .pred p; mbarrier.try_wait.parity.shared.b64 p, [%1], %2; selp.u32 %0, 1, 0, p; }" : "=r"(ok) : "r"(a), "r"(ph) : "memory");
  return ok != 0;
}
__device__ __forceinline__ void mbar_wait(uint32_t a, uint32_t ph) {
  if (mbar_try(a, ph)) return;
  int n = 0;
  while (!mbar_try(a, ph) && ++n < (1 << 22)) { }
}
__device__ __forceinline__ void bar_sync(int id, int n) { asm volatile("bar.sync %0, %1;" :: "r"(id), "r"(n) : "memory"); }
__device__ __forceinline__ void bar_arrive(int id, int n) { asm volatile("bar.arrive %0, %1;" :: "r"(id), "r"(n) : "memory"); }
__device__ __forceinline__ void fence_async_smem() { asm volatile("fence.proxy.async.shared::cta;" ::: "memory"); }
__device__ __forceinline__ unsigned ld_acquire(const unsigned* p) {
  unsigned v; asm volatile("ld.acquire.gpu.global.u32 %0, [%1];" : "=r"(v) : "l"(p) : "memory"); return v;
}
__device__ __forceinline__ void l2_prefetch(const void* p, uint32_t bytes) {
  asm volatile("cp.async.bulk.prefetch.L2.global [%0], %1;" :: "l"(p), "r"(bytes) : "memory");
}
__device__ __forceinline__ void red_release(unsigned* p, unsigned v) {
  asm volatile("red.release.gpu.global.add.u32 [%0], %1;" :: "l"(p), "r"(v) : "memory");
}
__device__ __forceinline__ void tma_load(uint32_t dst, const CUtensorMap* m, int c0, int c1, uint32_t bar) {
  asm volatile("cp.async.bulk.tensor.2d.shared::cluster.global.mbarrier::complete_tx::bytes [%0], [%1, {%3, %4}], [%2];"
               :: "r"(dst), "l"(m), "r"(bar), "r"(c0), "r"(c1) : "memory");
}
__device__ __forceinline__ void tma_store(const CUtensorMap* m, int c0, int c1, uint32_t src) {
  asm volatile("cp.async.bulk.tensor.2d.global.shared::cta.bulk_group [%0, {%2, %3}], [%1];"
               :: "l"(m), "r"(src), "r"(c0), "r"(c1) : "memory");
}
__device__ __forceinline__ void bulk_load(uint32_t dst, const void* src, uint32_t bytes, uint32_t bar) {
  asm volatile("cp.async.bulk.shared::cluster.global.mbarrier::complete_tx::bytes [%0], [%1], %2, [%3];"
               :: "r"(dst), "l"(src), "r"(bytes), "r"(bar) : "memory");
}
__device__ __forceinline__ void stsm4(uint32_t addr, uint32_t a, uint32_t b, uint32_t c, uint32_t d) {
  asm volatile("stmatrix.sync.aligned.m8n8.x4.shared.b16 [%0], {%1,%2,%3,%4};" :: "r"(addr), "r"(a), "r"(b), "r"(c), "r"(d) : "memory");
}
__device__ __forceinline__ uint4 ldsm4(uint32_t addr) {
  uint4 v; asm volatile("ldmatrix.sync.aligned.m8n8.x4.shared.b16 {%0,%1,%2,%3}, [%4];" : "=r"(v.x), "=r"(v.y), "=r"(v.z), "=r"(v.w) : "r"(addr) : "memory"); return v;
}
__device__ __forceinline__ void sts32(uint32_t addr, uint32_t v) { asm volatile("st.shared.u32 [%0], %1;" :: "r"(addr), "r"(v) : "memory"); }
__device__ __forceinline__ uint32_t lds32(uint32_t addr) { uint32_t v; asm volatile("ld.shared.u32 %0, [%1];" : "=r"(v) : "r"(addr) : "memory"); return v; }
__device__ __forceinline__ void sts128(uint32_t addr, uint4 v) {
  asm volatile("st.shared.v4.u32 [%0], {%1,%2,%3,%4};" :: "r"(addr), "r"(v.x), "r"(v.y), "r"(v.z), "r"(v.w) : "memory");
}
__device__ __forceinline__ uint4 lds128(uint32_t addr) {
  uint4 v; asm volatile("ld.shared.v4.u32 {%0,%1,%2,%3}, [%4];" : "=r"(v.x), "=r"(v.y), "=r"(v.z), "=r"(v.w) : "r"(addr) : "memory"); return v;
}
__device__ __forceinline__ void mma16816(float* d, const uint32_t* a, uint32_t b0, uint32_t b1) {
  asm volatile("mma.sync.aligned.m16n8k16.row.col.f32.bf16.bf16.f32 {%0,%1,%2,%3}, {%4,%5,%6,%7}, {%8,%9}, {%0,%1,%2,%3};"
               : "+f"(d[0]), "+f"(d[1]), "+f"(d[2]), "+f"(d[3]) : "r"(a[0]), "r"(a[1]), "r"(a[2]), "r"(a[3]), "r"(b0), "r"(b1));
}

__device__ __forceinline__ uint32_t desc_lo(uint32_t addr, uint32_t lbo) { return ((addr & 0x3FFFF) >> 4) | ((lbo >> 4) << 16); }
constexpr uint32_t DHI_SW128 = (1024 >> 4) | (1u << 30);

__device__ __forceinline__ uint4 attn_slow(uint32_t q0, uint32_t q1, uint32_t q2, uint32_t q3) {
  const int lane = threadIdx.x & 31, g = lane >> 2, t = lane & 3;
  const uint32_t q[4] = {q0, q1, q2, q3};
  const uint32_t* kb = reinterpret_cast<const uint32_t*>(g_kb);
  float m0 = -INFINITY, m1 = -INFINITY;
#pragma unroll 1
  for (int n0 = 0; n0 < SEQ; n0 += 8) {
    float s[4] = {0.f, 0.f, 0.f, 0.f};
    mma16816(s, q, __ldcg(kb + (n0 + g) * 8 + t), __ldcg(kb + (n0 + g) * 8 + 4 + t));
    m0 = fmaxf(m0, fmaxf(s[0], s[1]));
    m1 = fmaxf(m1, fmaxf(s[2], s[3]));
  }
  m0 = bfr(m0); m1 = bfr(m1);
  m0 = fmaxf(m0, __shfl_xor_sync(~0u, m0, 1)); m0 = fmaxf(m0, __shfl_xor_sync(~0u, m0, 2));
  m1 = fmaxf(m1, __shfl_xor_sync(~0u, m1, 1)); m1 = fmaxf(m1, __shfl_xor_sync(~0u, m1, 2));
  const float c = 0.25f * 1.4426950408889634f;
  float o[12];
#pragma unroll
  for (int i = 0; i < 12; i++) o[i] = 0.f;
  const unsigned short* vv = reinterpret_cast<const unsigned short*>(g_vb);
#pragma unroll 1
  for (int n0 = 0; n0 < SEQ; n0 += 16) {
    uint32_t p[4];
#pragma unroll
    for (int j = 0; j < 2; j++) {
      float s[4] = {0.f, 0.f, 0.f, 0.f};
      mma16816(s, q, __ldcg(kb + (n0 + 8 * j + g) * 8 + t), __ldcg(kb + (n0 + 8 * j + g) * 8 + 4 + t));
      p[2 * j]     = packbf(ex2f((bfr(s[0]) - m0) * c), ex2f((bfr(s[1]) - m0) * c));
      p[2 * j + 1] = packbf(ex2f((bfr(s[2]) - m1) * c), ex2f((bfr(s[3]) - m1) * c));
    }
#pragma unroll
    for (int pl = 0; pl < 2; pl++) {
      const unsigned short* vp = vv + (n0 + 2 * t) * 16 + pl * 8 + g;
      const uint32_t b0 = (uint32_t)__ldcg(vp) | ((uint32_t)__ldcg(vp + 16) << 16);
      const uint32_t b1 = (uint32_t)__ldcg(vp + 128) | ((uint32_t)__ldcg(vp + 144) << 16);
      mma16816(o + 4 * pl, p, b0, b1);
    }
    mma16816(o + 8, p, 0x3f803f80u, 0x3f803f80u);
  }
  const float i0 = rcpf(o[8]), i1 = rcpf(o[10]);
  return make_uint4(packbf(o[0] * i0, o[1] * i0), packbf(o[2] * i1, o[3] * i1),
                    packbf(o[4] * i0, o[5] * i0), packbf(o[6] * i1, o[7] * i1));
}

template<int D> __device__ __forceinline__ void dadd(uint64_t& d) { asm volatile("add.s64 %0, %0, %1;" : "+l"(d) : "n"(D)); }

template<int KNEXT, int VNEXT, bool NEWSTAGE>
__device__ __forceinline__ void attn_step(const uint32_t* q, float* o, float* s, uint32_t* h, uint64_t& dk, uint64_t& dv,
                                          uint32_t bar, int lane, uint32_t full_par, uint32_t na) {
  constexpr int NM = N32 / 4;
  uint32_t p[16];
  if (NEWSTAGE) mbar_wait(bar, full_par);
  WG_WAIT(0);
  fence_regs<N32 / 2>(s); fence_regs<16 - NM>(h);
  if (!NEWSTAGE) mbar_arrive_lane0(bar, lane);
#pragma unroll
  for (int i = 0; i < 4; i++) p[i] = packbf(ex2f(s[2 * i]), ex2f(s[2 * i + 1]));
#pragma unroll
  for (int i = 12; i < 16; i++) p[i] = exp2_poly(h[i - NM], na);
  WG_FENCE();
  pv24(o, p, dv); dadd<144>(dv);
  pv24(o, p + 12, dv); dadd<-48>(dv);
#pragma unroll
  for (int i = 8; i < 12; i++) p[i] = exp2_poly(h[i - NM], na);
#pragma unroll
  for (int i = 4; i < 8; i++) p[i] = packbf(ex2f(s[2 * i]), ex2f(s[2 * i + 1]));
  WG_FENCE();
  pv24(o, p + 8, dv); dadd<-48>(dv);
  dadd<N32 * 2>(dk);
  qk16<64 - N32>(h, q, dk); dadd<-N32 * 2>(dk);
  qk32<N32>(s, q, dk); dadd<KNEXT>(dk);
  pv24(o, p + 4, dv); dadd<VNEXT>(dv);
  WG_COMMIT();
}

struct Ring { int s, ph; };

template<int N, int AMODE>
__device__ __forceinline__ void gemm_pass(float* acc, int nkb, bool own, Ring& r, uint32_t sb, bool lane0) {
  const uint32_t bars = sb + SM_BAR;
  int sp = 0;
#pragma unroll 1
  for (int kb = 0; kb < nkb; kb++) {
    uint32_t aaddr = sb + SM_XN + (AMODE ? r.s : kb) * 8192;
    if (AMODE && own && (kb & 3) == 0) { mbar_wait(bars + (B_ORDY + (kb >> 2)) * 8, 0); aaddr = sb + SM_OT + (kb >> 2) * 8192; }
    mbar_wait(bars + (B_GFULL + r.s) * 8, r.ph);
    const uint32_t da = desc_lo(aaddr, 16);
    const uint32_t db = desc_lo(sb + SM_RING + r.s * GSTAGE, 8192);
    WG_FENCE();
#pragma unroll
    for (int j = 0; j < 4; j++) {
      gemm_ss<64>(acc, mkdesc(da + j * 2, DHI_SW128), mkdesc(db + j * 128, DHI_SW128), (kb | j) != 0);
      if (N == 128) gemm_ss<64>(acc + 32, mkdesc(da + j * 2, DHI_SW128), mkdesc(db + 512 + j * 128, DHI_SW128), (kb | j) != 0);
    }
    WG_COMMIT();
    if (kb > 0) {
      WG_WAIT(1);
      if (lane0) mbar_arrive(bars + (B_GEMPTY + sp) * 8);
    }
    sp = r.s;
    if (++r.s == NGS) { r.s = 0; r.ph ^= 1; }
  }
  WG_WAIT(0);
  fence_regs<N / 2>(acc);
  if (lane0) mbar_arrive(bars + (B_GEMPTY + sp) * 8);
}

template<int N>
__device__ __forceinline__ void ffn1_epilogue(const float* acc, uint32_t sb, int j, int tw) {
  const int lane = tw & 31, w = tw >> 5, t = lane & 3;
  if (j > 0) mbar_wait(sb + SM_BAR + B_HFREE * 8, (j - 1) & 1);
  const int row = 16 * w + (lane & 7) + ((lane >> 3) & 1) * 8;
  const uint32_t rbase = sb + SM_STG + row * 128;
  const uint32_t bb = sb + SM_BIAS + (128 * j + 2 * t) * 2;
#pragma unroll
  for (int jj = 0; jj < N / 8; jj += 2) {
    uint32_t v[4];
#pragma unroll
    for (int u = 0; u < 2; u++) {
      const uint32_t b = lds32(bb + (jj + u) * 16);
      uint32_t r0 = badd2_relu(packbf(acc[4 * (jj + u)], acc[4 * (jj + u) + 1]), b);
      uint32_t r1 = badd2_relu(packbf(acc[4 * (jj + u) + 2], acc[4 * (jj + u) + 3]), b);
      v[2 * u] = bmul2(r0, r0); v[2 * u + 1] = bmul2(r1, r1);
    }
    const int ch = jj + (lane >> 4);
    stsm4(rbase + (ch >> 3) * 8192 + (((ch & 7) ^ (row & 7)) << 4), v[0], v[1], v[2], v[3]);
  }
  fence_async_smem();
  __syncwarp();
  if (lane == 0) mbar_arrive(sb + SM_BAR + B_HRDY * 8);
}

__device__ __forceinline__ void spin_until(const unsigned* p, unsigned want) {
  int spins = 0;
  while (ld_acquire(p) != want && ++spins < (1 << 22)) __nanosleep(20);
}
__device__ __forceinline__ void st_release(unsigned* p, unsigned v) {
  asm volatile("st.release.gpu.global.u32 [%0], %1;" :: "l"(p), "r"(v) : "memory");
}

__global__ void __launch_bounds__(NTHREADS, 1)
fused_kernel(const __grid_constant__ Params P, const WPtrs W, const __nv_bfloat16* __restrict__ wk, const __nv_bfloat16* __restrict__ wv,
             const __nv_bfloat16* __restrict__ b1, const __nv_bfloat16* __restrict__ b2) {
  extern __shared__ unsigned char smem_raw[];
  const uint32_t sb = ((uint32_t)__cvta_generic_to_shared(smem_raw) + 1023u) & ~1023u;
  const uint32_t bars = sb + SM_BAR;
  const int tid = threadIdx.x, warp = __shfl_sync(~0u, tid >> 5, 0), lane = tid & 31;
  const int cta = blockIdx.x, rb = cta >> 2, c = cta & 3, row0 = rb * 64;
  if (warp < 16) {
    const int wg = warp >> 2, ww = warp & 3;
    {
      const int row = 4 * warp + (lane >> 3);
      const uint32_t addr = sb + SM_XN + row * 128 + (((lane & 7) ^ (row & 7)) << 4);
      uint4 xv[8];
#pragma unroll
      for (int i = 0; i < 8; i++) xv[i] = __ldg(reinterpret_cast<const uint4*>(W.x + (size_t)(row0 + row) * DM) + i * 8 + (lane & 7));
      asm volatile("setmaxnreg.inc.sync.aligned.u32 88;");
      bar_sync(6, NTHREADS);
      const uint32_t* u = reinterpret_cast<const uint32_t*>(xv);
      float a1[2] = {0.f, 0.f}, a2[4] = {0.f, 0.f, 0.f, 0.f};
#pragma unroll
      for (int i = 0; i < 32; i++) {
        const float a = bflo(u[i]), b = bfhi(u[i]);
        a1[i & 1] += a + b;
        a2[(i & 1) * 2] = fmaf(a, a, a2[(i & 1) * 2]); a2[(i & 1) * 2 + 1] = fmaf(b, b, a2[(i & 1) * 2 + 1]);
      }
      float s1 = a1[0] + a1[1], s2 = (a2[0] + a2[1]) + (a2[2] + a2[3]);
#pragma unroll
      for (int o = 4; o; o >>= 1) { s1 += __shfl_xor_sync(~0u, s1, o); s2 += __shfl_xor_sync(~0u, s2, o); }
      if (tid == 0 && s2 != -1.0f) { mbar_arrive(bars + B_XIN * 8); }
      const float dm = s1 * (1.0f / DM);
      const float var = fmaxf(fmaf(-dm, dm, s2 * (1.0f / DM)), 0.f);
      const uint32_t nmb = packbf(-dm, -dm);
      const float inv = rcpf(bfr(sqrtaf(bfr(bfr(var) + 1e-5f))));
      const uint32_t ihi = packbf(inv, inv);
      const float il = inv - bflo(ihi);
      const uint32_t ilo = packbf(il, il);
#pragma unroll
      for (int i = 0; i < 8; i++) {
        uint32_t o4[4];
#pragma unroll
        for (int k = 0; k < 4; k++) {
          const uint32_t d = badd2(u[4 * i + k], nmb);
          o4[k] = (k & 1) ? packbf(bflo(d) * inv, bfhi(d) * inv) : bfma2(d, ihi, bmul2(d, ilo));
        }
        sts128(addr + i * 8192, make_uint4(o4[0], o4[1], o4[2], o4[3]));
      }
    }
    fence_async_smem();
    if (wg != 0) {
      bar_arrive(5, 736);
    } else {
      const int g = lane >> 2, t = lane & 3;
      float kv[16];
#pragma unroll
      for (int i = 0; i < 16; i++) kv[i] = 0.f;
      uint32_t db = desc_lo(sb + SM_KVR, 128), da = desc_lo(sb + SM_XN, 16);
      bar_sync(5, 736);
#pragma unroll 1
      for (int kb = 0; kb < 8; kb++) {
        WG_FENCE();
#pragma unroll
        for (int j = 0; j < 4; j++)
          gemm_ss<32>(kv, mkdesc(da + j * 2, DHI_SW128), mkdesc(db + j * 16, 8192 >> 4), 1);
        da += 8192 >> 4; db += 64;
      }
      WG_COMMIT();
      WG_WAIT(0);
      fence_regs<16>(kv);
      bar_sync(7, 128);
      if (ww == c) {
        uint32_t kbf[4];
        const int key0 = row0 + 16 * c;
        unsigned char* blk = g_kv + (key0 >> 7) * KSTAGE;
        const int grp0 = (key0 & 127) >> 3;
        unsigned char* vblk = blk + 4096 + (grp0 >> 1) * 768;
#pragma unroll
        for (int rr = 0; rr < 2; rr++) {
          const float vs = (((key0 + 8 * rr) & 63) < N32) ? POLY_SCALE : 1.0f;
#pragma unroll
          for (int j = 0; j < 2; j++) {
            kbf[2 * rr + j] = packbf(kv[4 * j + 2 * rr], kv[4 * j + 2 * rr + 1]);
            *reinterpret_cast<uint32_t*>(blk + (grp0 + rr) * 256 + j * 128 + lane * 4) = packh(bflo(kbf[2 * rr + j]), bfhi(kbf[2 * rr + j]));
            *reinterpret_cast<uint32_t*>(vblk + j * 256 + rr * 128 + lane * 4) = packbf(kv[8 + 4 * j + 2 * rr] * vs, kv[8 + 4 * j + 2 * rr + 1] * vs);
          }
          *reinterpret_cast<uint32_t*>(vblk + 512 + rr * 128 + lane * 4) = packbf(vs, vs);
        }
        asm volatile("fence.proxy.async.global;" ::: "memory");
        __syncwarp();
        if (lane == 0) { red_release(&g_cnt_kv, 1); mbar_arrive(bars + B_KVPUB * 8); }
        float kn[2] = {0.f, 0.f}, vm = 0.f;
#pragma unroll
        for (int rr = 0; rr < 2; rr++) {
          const int key = key0 + 8 * rr + g;
#pragma unroll
          for (int jj = 0; jj < 2; jj++) {
            const float a = bflo(kbf[2 * rr + jj]), b = bfhi(kbf[2 * rr + jj]);
            kn[rr] += a * a + b * b;
            reinterpret_cast<uint32_t*>(g_kb)[key * 8 + jj * 4 + t] = kbf[2 * rr + jj];
            const float v0 = kv[8 + 4 * jj + 2 * rr], v1 = kv[8 + 4 * jj + 2 * rr + 1];
            reinterpret_cast<uint32_t*>(g_vb)[key * 8 + jj * 4 + t] = packbf(v0, v1);
            vm = fmaxf(vm, fmaxf(fabsf(v0), fabsf(v1)));
            if (!(v0 == v0) || !(v1 == v1)) vm = INFINITY;
          }
          kn[rr] += __shfl_xor_sync(~0u, kn[rr], 1); kn[rr] += __shfl_xor_sync(~0u, kn[rr], 2);
          if (!(kn[rr] == kn[rr])) kn[rr] = INFINITY;
        }
        float km = fmaxf(kn[0], kn[1]);
#pragma unroll
        for (int o = 16; o; o >>= 1) { km = fmaxf(km, __shfl_xor_sync(~0u, km, o)); vm = fmaxf(vm, __shfl_xor_sync(~0u, vm, o)); }
        if (lane == 0) { g_kmax[cta] = km; g_vmax[cta] = vm; }
        __syncwarp();
        if (lane == 0) mbar_arrive(bars + B_AUX * 8);
      }
    }

    const bool lane0 = lane == 0;
    const int qrow = 16 * ww + (lane & 7) + ((lane >> 3) & 1) * 8;
    const uint32_t qo = sb + SM_OT + qrow * 128 + (((2 * wg + (lane >> 4)) ^ (qrow & 7)) << 4);
    const uint32_t na = 0xb5a0b5a0u;
    const uint64_t dw = mkdesc(desc_lo(sb + SM_KVR, 128), 256 >> 4);
#pragma unroll 1
    for (int p = 0; p < 2; p++) {
      uint32_t qs[4], q[4];
      mbar_wait(bars + (B_QRDY + p) * 8, 0);
      { const uint4 v = ldsm4(qo + p * 8192); qs[0] = v.x; qs[1] = v.y; qs[2] = v.z; qs[3] = v.w; }
      const float qc = 0.25f * 1.4426950408889634f;
#pragma unroll
      for (int i = 0; i < 4; i++) q[i] = packh(bflo(qs[i]) * qc, bfhi(qs[i]) * qc);
      float qn0, qn1;
      {
        float a;
        a = bflo(qs[0]) * qc; qn0 = a * a; a = bfhi(qs[0]) * qc; qn0 += a * a;
        a = bflo(qs[2]) * qc; qn0 += a * a; a = bfhi(qs[2]) * qc; qn0 += a * a;
        a = bflo(qs[1]) * qc; qn1 = a * a; a = bfhi(qs[1]) * qc; qn1 += a * a;
        a = bflo(qs[3]) * qc; qn1 += a * a; a = bfhi(qs[3]) * qc; qn1 += a * a;
        qn0 += __shfl_xor_sync(~0u, qn0, 1); qn0 += __shfl_xor_sync(~0u, qn0, 2);
        qn1 += __shfl_xor_sync(~0u, qn1, 1); qn1 += __shfl_xor_sync(~0u, qn1, 2);
      }
      const float qn = (qn0 > qn1 || !(qn0 == qn0)) ? qn0 : qn1;
      float o[12];
#pragma unroll
      for (int i = 0; i < 12; i++) o[i] = 0.f;
      {
        float s[N32 / 2]; uint32_t h[16 - N32 / 4];
        uint64_t dk = dw, dv = dw + 256;
        fence_regs<12>(o); fence_regs<4>(q);
        mbar_wait(bars + B_KFULL * 8, 0);
        WG_FENCE();
        qk32<N32>(s, q, dk); dadd<N32 * 2>(dk);
        qk16<64 - N32>(h, q, dk); dadd<128 - N32 * 2>(dk);
        WG_COMMIT();
#pragma unroll 1
        for (int st = 0; st < 16; st++) {
          const int slot = st & (NKS - 1);
          attn_step<640 - 128, 144, false>(q, o, s, h, dk, dv, bars + B_KEMPTY * 8 + (((st + NKS - 1) * 8) & (NKS * 8 - 8)), lane, 0, na);
          if (slot == NKS - 1) dadd<-NKS * 640>(dk);
          attn_step<128, 144 + 256, true>(q, o, s, h, dk, dv, bars + B_KFULL * 8 + (((st + 1) * 8) & (NKS * 8 - 8)), lane, ((st + 1) / NKS) & 1, na);
          if (slot == NKS - 1) dadd<-NKS * 640>(dv);
        }
        WG_WAIT(0);
        fence_regs<N32 / 2>(s); fence_regs<16 - N32 / 4>(h);
      }
      WG_WAIT(0);
      fence_regs<12>(o);

      const float km = __uint_as_float(lds32(bars + B_GUARD * 8)), vm = __uint_as_float(lds32(bars + B_GUARD * 8 + 4));
      const bool ok = (qn * km <= 1590.f) && (qn <= 1.0e6f) && (km <= 1.0e6f)
                      && (vm <= 1.0e12f) && (vm >= 1.0e-12f);
      uint4 ov;
      if (__all_sync(~0u, ok)) {
        const float i0 = rcpf(o[8]), i1 = rcpf(o[10]);
        ov = make_uint4(packbf(o[0] * i0, o[1] * i0), packbf(o[2] * i1, o[3] * i1),
                        packbf(o[4] * i0, o[5] * i0), packbf(o[6] * i1, o[7] * i1));
      } else {
        const uint4 v = ldsm4(qo + p * 8192);
        ov = attn_slow(v.x, v.y, v.z, v.w);
      }
      __syncwarp();
      stsm4(qo + p * 8192, ov.x, ov.y, ov.z, ov.w);
      fence_async_smem();
      __syncwarp();
      if (lane0) mbar_arrive(bars + (B_ORDY + p) * 8);
    }
    mbar_wait(bars + B_ZRDY * 8, 0);
#pragma unroll
    for (int i = 0; i < 2; i++) {
      const uint32_t ad = sb + SM_STG + i * 8192 + tid * 16;
      const uint4 zv = lds128(ad);
      uint32_t z[4] = {zv.x, zv.y, zv.z, zv.w};
#pragma unroll
      for (int u = 0; u < 4; u++) {
        const float z0 = bflo(z[u]), z1 = bfhi(z[u]);
        z[u] = packbf(z0 * rcpf(1.0f + ex2f(z0 * -1.4426950408889634f)), z1 * rcpf(1.0f + ex2f(z1 * -1.4426950408889634f)));
      }
      sts128(ad, make_uint4(z[0], z[1], z[2], z[3]));
    }
    __syncwarp();
    if (lane0) mbar_arrive(bars + B_GRDY * 8);
  } else if (warp < 20) {
    asm volatile("setmaxnreg.inc.sync.aligned.u32 104;");
    const int tw = tid - 512, w = warp - 16, t = lane & 3;
    const bool lane0 = lane == 0;
    Ring r{0, 0};
    bar_arrive(6, NTHREADS);
    {
      uint4 wv4[16];
#pragma unroll
      for (int i = 0; i < 16; i++) wv4[i] = __ldg(reinterpret_cast<const uint4*>(i < 8 ? wk : wv) + (i & 7) * 128 + tw);
#pragma unroll
      for (int i = 0; i < 16; i++)
        sts128(sb + SM_KVR + ((i >> 3) * 2 + (tw & 1)) * 8192 + ((i & 7) * 64 + (tw >> 1)) * 16, wv4[i]);
      fence_async_smem();
    }
    float acc[64];
#pragma unroll
    for (int i = 0; i < 64; i++) acc[i] = 0.f;
    bar_sync(5, 736);
    const int srow = 16 * w + (lane & 7) + ((lane >> 3) & 1) * 8;
#pragma unroll 1
    for (int p = 0; p < 2; p++) {
      int sp = 0;
#pragma unroll 1
      for (int kb = 0; kb < 4; kb++) {
        mbar_wait(bars + (B_GFULL + r.s) * 8, r.ph);
        const uint32_t da = desc_lo(sb + SM_XN + kb * 16384, 16);
        const uint32_t db = desc_lo(sb + SM_RING + r.s * GSTAGE, 8192);
        WG_FENCE();
#pragma unroll
        for (int j = 0; j < 8; j++)
          gemm_ss<64>(acc, mkdesc(da + (j >> 2) * 512 + (j & 3) * 2, DHI_SW128), mkdesc(db + j * 128, DHI_SW128), (kb | j) != 0);
        WG_COMMIT();
        if (kb > 0) {
          WG_WAIT(1);
          if (lane0) mbar_arrive(bars + (B_GEMPTY + sp) * 8);
        }
        sp = r.s;
        if (++r.s == NGS) { r.s = 0; r.ph ^= 1; }
      }
      WG_WAIT(0);
      fence_regs<32>(acc);
      if (lane0) mbar_arrive(bars + (B_GEMPTY + sp) * 8);
#pragma unroll
      for (int jj = 0; jj < 8; jj += 2)
        stsm4(sb + SM_OT + p * 8192 + srow * 128 + (((jj + (lane >> 4)) ^ (srow & 7)) << 4),
              packbf(acc[4 * jj], acc[4 * jj + 1]), packbf(acc[4 * jj + 2], acc[4 * jj + 3]),
              packbf(acc[4 * jj + 4], acc[4 * jj + 5]), packbf(acc[4 * jj + 6], acc[4 * jj + 7]));
      __syncwarp();
      if (lane0) mbar_arrive(bars + (B_QRDY + p) * 8);
    }
    mbar_wait(bars + B_BIAS * 8, 0);
#pragma unroll 1
    for (int j = 0; j < 3; j++) {
      gemm_pass<128, 0>(acc, 8, false, r, sb, lane0);
      ffn1_epilogue<128>(acc, sb, j, tw);
    }
    gemm_pass<64, 0>(acc, 8, false, r, sb, lane0);
    ffn1_epilogue<64>(acc, sb, 3, tw);
#pragma unroll 1
    for (int j = 0; j < 2; j++) {
      gemm_pass<128, 1>(acc, j ? 8 : 28, j != 0, r, sb, lane0);
      if (j == 0) {
        const uint32_t bb = sb + SM_BIAS + (448 + 2 * t) * 2;
#pragma unroll
        for (int jj = 0; jj < 16; jj += 2) {
          uint32_t z[4];
#pragma unroll
          for (int u = 0; u < 4; u++) z[u] = badd2(packbf(acc[4 * jj + 2 * u], acc[4 * jj + 2 * u + 1]), lds32(bb + (jj + (u >> 1)) * 16));
          sts128(sb + SM_STG + jj * 1024 + tw * 16, make_uint4(z[0], z[1], z[2], z[3]));
        }
        __syncwarp();
        if (lane0) mbar_arrive(bars + B_ZRDY * 8);
        mbar_wait(bars + B_XT * 8, 0);
      }
    }
    mbar_wait(bars + B_GRDY * 8, 0);
    {
#pragma unroll
      for (int j = 0; j < 16; j += 2) {
        const int ch = j + (lane >> 4);
        const uint32_t off = srow * 128 + (ch >> 3) * 8192 + (((ch & 7) ^ (srow & 7)) << 4);
        const uint4 xx = ldsm4(sb + SM_XT + off);
        const uint4 gv = lds128(sb + SM_STG + j * 1024 + tw * 16);
        stsm4(sb + SM_OUT + off,
              badd2(xx.x, bmul2(packbf(acc[4 * j], acc[4 * j + 1]), gv.x)),
              badd2(xx.y, bmul2(packbf(acc[4 * j + 2], acc[4 * j + 3]), gv.y)),
              badd2(xx.z, bmul2(packbf(acc[4 * j + 4], acc[4 * j + 5]), gv.z)),
              badd2(xx.w, bmul2(packbf(acc[4 * j + 6], acc[4 * j + 7]), gv.w)));
      }
      fence_async_smem();
      bar_sync(4, 128);
      if (tw == 0) {
        tma_store(&P.out, 128 * c, row0, sb + SM_OUT);
        tma_store(&P.out, 128 * c + 64, row0, sb + SM_OUT + 8192);
        asm volatile("cp.async.bulk.commit_group;" ::: "memory");
        asm volatile("cp.async.bulk.wait_group.read 0;" ::: "memory");
      }
    }
  } else {
    asm volatile("setmaxnreg.dec.sync.aligned.u32 24;");
    if (warp == 20) {
      if (lane == 0) {
        mbar_init(bars + B_XIN * 8, 1);
#pragma unroll 1
        for (int i = 0; i < NGS; i++) { mbar_init(bars + (B_GFULL + i) * 8, 1); mbar_init(bars + (B_GEMPTY + i) * 8, 4); }
#pragma unroll 1
        for (int i = 0; i < NKS; i++) { mbar_init(bars + (B_KFULL + i) * 8, 1); mbar_init(bars + (B_KEMPTY + i) * 8, 16); }
        mbar_init(bars + B_XT * 8, 1);
        mbar_init(bars + B_HRDY * 8, 4);
        mbar_init(bars + B_HFREE * 8, 1);
        mbar_init(bars + B_ORDY * 8, 16); mbar_init(bars + (B_ORDY + 1) * 8, 16);
        mbar_init(bars + B_QRDY * 8, 4); mbar_init(bars + (B_QRDY + 1) * 8, 4);
        mbar_init(bars + B_BIAS * 8, 1);
        mbar_init(bars + B_KVPUB * 8, 1);
        mbar_init(bars + B_HPUB * 8, 1);
        mbar_init(bars + B_ZRDY * 8, 4);
        mbar_init(bars + B_GRDY * 8, 16);
        mbar_init(bars + B_AUX * 8, 1);
        asm volatile("fence.mbarrier_init.release.cluster;" ::: "memory");
        fence_async_smem();
        mbar_expect(bars + B_BIAS * 8, 1152);
        bulk_load(sb + SM_BIAS, b1 + 448 * c, 896, bars + B_BIAS * 8);
        bulk_load(sb + SM_BIAS + 896, b2 + 128 * c, 256, bars + B_BIAS * 8);
      }
      __syncwarp();
      bar_arrive(6, NTHREADS);
      if (lane == 0) {
        int s = 0, ph = 1;
#pragma unroll 1
        for (int gb = 0; gb < NKBLK; gb++) {
          const CUtensorMap* m; int n = 128 * c, k, n2, k2; uint32_t bytes = 24576;
          if (gb < 8)       { m = &P.wq; n += 64 * (gb >> 2); k = 128 * (gb & 3); bytes = 16384; }
          else if (gb < 40) { m = &P.w1; n = 448 * c + 128 * ((gb - 8) >> 3); k = 64 * (gb & 7); bytes = gb >= 32 ? 8192 : 16384; }
          else if (gb < 68) { const int u = gb - 40; m = &P.w2; k = 448 * ((c + u / 7) & 3) + 64 * (u % 7); }
          else              { const int u = gb - 68; m = &P.wo; k = 128 * ((c + u) & 3) + 64 * (u >> 2); if ((u & 3) == 0) bytes = 16384; }
          if (gb < 8) { n2 = n; k2 = k + 64; } else { n2 = n + 64; k2 = k; }
          const uint32_t fb = bars + (B_GFULL + s) * 8, dst = sb + SM_RING + s * GSTAGE;
          mbar_wait(bars + (B_GEMPTY + s) * 8, ph);
          mbar_expect(fb, bytes);
          tma_load(dst, m, n, k, fb);
          if (bytes != 8192) tma_load(dst + 8192, m, n2, k2, fb);
          if (++s == NGS) { s = 0; ph ^= 1; }
        }
      }
    } else {
      if (warp == 21 && lane < 8)
        asm volatile("prefetch.tensormap [%0];" :: "l"(reinterpret_cast<const CUtensorMap*>(&P) + lane) : "memory");
      const unsigned tag = (__ldcg(&g_cnt_kv) >> 7) + 1;
      bar_sync(6, NTHREADS);
      sts32(bars + B_TAG * 8, tag);
      bar_arrive(5, 736);
      if (warp == 23 && lane < 4) {
        mbar_wait(bars + B_XIN * 8, 0);
        const __nv_bfloat16* wp = lane == 0 ? W.wq : lane == 1 ? W.w1 : lane == 2 ? W.w2 : W.wo;
        const uint32_t bytes = (lane == 1 || lane == 2) ? DM * FF * 2 / NCTA : DM * DM * 2 / NCTA;
        l2_prefetch(reinterpret_cast<const char*>(wp) + (size_t)cta * bytes, bytes);
      }
      __syncwarp();
      if (warp == 21) {
        if (lane == 0) {
          int s = 40 % NGS, ph = ((40 / NGS) - 1) & 1;
#pragma unroll 1
          for (int u = 0; u < 28; u++) {
            const int cc = (c + u / 7) & 3;
            if (u == 0) {
              mbar_wait(bars + B_HPUB * 8, 0);
              mbar_expect(bars + B_XT * 8, 16384);
              tma_load(sb + SM_XT, &P.x, 128 * c, row0, bars + B_XT * 8);
              tma_load(sb + SM_XT + 8192, &P.x, 128 * c + 64, row0, bars + B_XT * 8);
            } else if (u % 7 == 0) spin_until(&g_tag_h[rb * 4 + cc], tag);
            mbar_wait(bars + (B_GEMPTY + s) * 8, ph);
            tma_load(sb + SM_AR + s * 8192, &P.h, 448 * cc + 64 * (u % 7), row0, bars + (B_GFULL + s) * 8);
            if (++s == NGS) { s = 0; ph ^= 1; }
          }
        }
        __syncwarp();
#pragma unroll 1
        for (int p = 0; p < 2; p++) {
          bool pend = lane >= 1 && lane <= 3;
          const int ga = 68 + 4 * p + lane, s = ga % NGS, cc = (c + lane) & 3;
          if (pend) mbar_wait(bars + (B_GEMPTY + s) * 8, ((ga / NGS) - 1) & 1);
          mbar_wait(bars + (B_ORDY + p) * 8, 0);
          int spins = 0;
          while (__any_sync(~0u, pend) && ++spins < (1 << 22)) {
            if (pend && ld_acquire(&g_tag_o[(rb * 4 + cc) * 2 + p]) == tag) {
              tma_load(sb + SM_AR + s * 8192, &P.o, 128 * cc + 64 * p, row0, bars + (B_GFULL + s) * 8);
              pend = false;
            }
            __nanosleep(20);
          }
        }
      } else if (warp == 22) {
        if (lane == 0) {
          mbar_wait(bars + B_KVPUB * 8, 0);
          spin_until(&g_cnt_kv, tag << 7);
#pragma unroll 1
          for (int i = 0; i < NKS; i++) {
            mbar_expect(bars + (B_KFULL + i) * 8, KSTAGE);
            bulk_load(sb + SM_KVR + i * KSTAGE, g_kv + i * KSTAGE, KSTAGE, bars + (B_KFULL + i) * 8);
          }
        }
        if (lane == 0) {
          mbar_wait(bars + B_AUX * 8, 0);
          red_release(&g_cnt_aux, 1);
          spin_until(&g_cnt_aux, tag << 7);
        }
        __syncwarp();
        const float4 k4 = __ldcg(reinterpret_cast<const float4*>(g_kmax) + lane);
        const float4 v4 = __ldcg(reinterpret_cast<const float4*>(g_vmax) + lane);
        float km = fmaxf(fmaxf(k4.x, k4.y), fmaxf(k4.z, k4.w)), vm = fmaxf(fmaxf(v4.x, v4.y), fmaxf(v4.z, v4.w));
#pragma unroll
        for (int o = 16; o; o >>= 1) { km = fmaxf(km, __shfl_xor_sync(~0u, km, o)); vm = fmaxf(vm, __shfl_xor_sync(~0u, vm, o)); }
        if (lane == 0) {
          sts32(bars + B_GUARD * 8, __float_as_uint(km));
          sts32(bars + B_GUARD * 8 + 4, __float_as_uint(vm));
          mbar_wait(bars + (B_KEMPTY + NKS - 1) * 8, 0);
#pragma unroll 1
          for (int i = NKS; i < 33; i++) {
            const int s = i & (NKS - 1);
            const int j = i >= LEADFROM ? i + 1 : i;
            if (i == LEADFROM) mbar_wait(bars + (B_KEMPTY + s) * 8, (((i + 1) / NKS) - 1) & 1);
            mbar_wait(bars + (B_KEMPTY + (j & (NKS - 1))) * 8, (((j + 1) / NKS) - 1) & 1);
            mbar_expect(bars + (B_KFULL + s) * 8, KSTAGE);
            bulk_load(sb + SM_KVR + s * KSTAGE, g_kv + (i & 15) * KSTAGE, KSTAGE, bars + (B_KFULL + s) * 8);
          }
        }
      } else if (lane == 0) {
        int hj = 0, op = 0, spins = 0;
        while (hj < 4 || op < 2) {
          if (hj < 4 && mbar_test(bars + B_HRDY * 8, hj & 1)) {
            tma_store(&P.h, 448 * c + 128 * hj, row0, sb + SM_STG);
            if (hj < 3) tma_store(&P.h, 448 * c + 128 * hj + 64, row0, sb + SM_STG + 8192);
            asm volatile("cp.async.bulk.commit_group;" ::: "memory");
            if (hj < 3) {
              asm volatile("cp.async.bulk.wait_group.read 0;" ::: "memory");
              mbar_arrive(bars + B_HFREE * 8);
            } else {
              asm volatile("cp.async.bulk.wait_group 0;" ::: "memory");
              mbar_arrive(bars + B_HPUB * 8);
              st_release(&g_tag_h[cta], tag);
            }
            hj++;
          } else if (op < 2 && (hj == 4 ? mbar_try(bars + (B_ORDY + op) * 8, 0) : mbar_test(bars + (B_ORDY + op) * 8, 0))) {
            tma_store(&P.o, 128 * c + 64 * op, row0, sb + SM_OT + op * 8192);
            asm volatile("cp.async.bulk.commit_group;" ::: "memory");
            asm volatile("cp.async.bulk.wait_group 0;" ::: "memory");
            st_release(&g_tag_o[cta * 2 + op], tag);
            op++;
          } else {
            if (hj < 4) __nanosleep(400);
            if (++spins > (1 << 24)) break;
          }
        }
      }
    }
  }
}

typedef CUresult (*EncodeFn)(CUtensorMap*, CUtensorMapDataType, cuuint32_t, void*, const cuuint64_t*, const cuuint64_t*,
                             const cuuint32_t*, const cuuint32_t*, CUtensorMapInterleave, CUtensorMapSwizzle,
                             CUtensorMapL2promotion, CUtensorMapFloatOOBfill);

void make_map(EncodeFn fn, CUtensorMap* m, const void* ptr, uint64_t cols, uint64_t rows) {
  cuuint64_t dims[2] = {cols, rows};
  cuuint64_t strides[1] = {cols * 2};
  cuuint32_t box[2] = {64, 64};
  cuuint32_t es[2] = {1, 1};
  fn(m, CU_TENSOR_MAP_DATA_TYPE_BFLOAT16, 2, const_cast<void*>(ptr), dims, strides, box, es,
     CU_TENSOR_MAP_INTERLEAVE_NONE, CU_TENSOR_MAP_SWIZZLE_128B, CU_TENSOR_MAP_L2_PROMOTION_L2_256B,
     CU_TENSOR_MAP_FLOAT_OOB_FILL_NONE);
}

}

extern "C" void kernel_launch(void* const* d_in, const int* in_sizes, int n_in, void* d_out, int out_size) {
  (void)in_sizes; (void)n_in; (void)out_size;
  const __nv_bfloat16* x  = (const __nv_bfloat16*)d_in[0];
  const __nv_bfloat16* wq = (const __nv_bfloat16*)d_in[1];
  const __nv_bfloat16* wk = (const __nv_bfloat16*)d_in[2];
  const __nv_bfloat16* wv = (const __nv_bfloat16*)d_in[3];
  const __nv_bfloat16* wo = (const __nv_bfloat16*)d_in[4];
  const __nv_bfloat16* w1 = (const __nv_bfloat16*)d_in[6];
  const __nv_bfloat16* b1 = (const __nv_bfloat16*)d_in[7];
  const __nv_bfloat16* w2 = (const __nv_bfloat16*)d_in[8];
  const __nv_bfloat16* b2 = (const __nv_bfloat16*)d_in[9];

  void* fnp = nullptr;
  cudaDriverEntryPointQueryResult qr;
  cudaGetDriverEntryPoint("cuTensorMapEncodeTiled", &fnp, cudaEnableDefault, &qr);
  EncodeFn fn = (EncodeFn)fnp;
  void *hp = nullptr, *op = nullptr;
  cudaGetSymbolAddress(&hp, g_h);
  cudaGetSymbolAddress(&op, g_o);

  Params P;
  make_map(fn, &P.wq, wq, DM, DM);
  make_map(fn, &P.w1, w1, FF, DM);
  make_map(fn, &P.w2, w2, DM, FF);
  make_map(fn, &P.wo, wo, DM, DM);
  make_map(fn, &P.h, hp, FF, SEQ);
  make_map(fn, &P.o, op, DM, SEQ);
  make_map(fn, &P.x, x, DM, SEQ);
  make_map(fn, &P.out, d_out, DM, SEQ);

  cudaFuncSetAttribute(fused_kernel, cudaFuncAttributeMaxDynamicSharedMemorySize, SMEM_BYTES);
  fused_kernel<<<NCTA, NTHREADS, SMEM_BYTES, cudaStreamPerThread>>>(P, WPtrs{wq, w1, w2, wo, x}, wk, wv, b1, b2);
}
```
